```python
import torch

def _softmax(x, axis=-1):
    return torch.softmax(x, dim=axis)
def _gelu(x):
    return torch.nn.functional.gelu(x, approximate="tanh")
def _silu(x):
    return torch.nn.functional.silu(x)
def _sigmoid(x):
    return torch.sigmoid(x)
def _layernorm(x, axis=-1, eps=1e-5):
    m = x.mean(dim=axis, keepdim=True)
    v = x.var(dim=axis, keepdim=True, unbiased=False)
    return (x - m) / torch.sqrt(v + eps)
def _scatter_add(tgt, idx, src, axis=0):
    return tgt.clone().index_add_(axis, idx, src)
def _segment_sum(src, seg, n):
    out = torch.zeros((n,) + src.shape[1:], dtype=src.dtype)
    return out.index_add_(0, seg, src)
def _pad(x, pw):
    flat = tuple(v for pair in reversed(pw) for v in pair)
    return torch.nn.functional.pad(x, flat)

kernel_name = 'standalone__gqa_softmax__sampling'

def setup_inputs():

    _w = (lambda a: (lambda t: t.to(torch.bfloat16) if t.is_floating_point() else t)(torch.as_tensor(a)))
    B, Hq, Hkv, Sq, Sk, D = 8, 32, 8, 4, 8192, 128
    return {
        "q": _w((lambda *s: torch.randn(*s, dtype=torch.bfloat16) * 0.8)(B, Hq, Sq, D)),
        "k": _w((lambda *s: torch.randn(*s, dtype=torch.bfloat16) * 0.8)(B, Hkv, Sk, D)),
        "v": _w((lambda *s: torch.randn(*s, dtype=torch.bfloat16) * 0.05)(B, Hkv, Sk, D)),
    }

def reference(q, k, v):
    B, Hq, Sq, D = q.shape
    Hkv = k.shape[1]
    rep = Hq // Hkv
    k = (lambda x, n, axis: torch.repeat_interleave(x, n, dim=axis))(k, rep, axis=1)
    v = (lambda x, n, axis: torch.repeat_interleave(x, n, dim=axis))(v, rep, axis=1)
    scale = D ** -0.5
    scores = torch.einsum("bhqd,bhkd->bhqk", q, k) * scale
    p = _softmax(scores, axis=-1)
    return torch.einsum("bhqk,bhkd->bhqd", p, v)
```

```cpp
#include <cuda_runtime.h>
#include <cuda_bf16.h>
#include <stdint.h>

#define GQA_NW 8
#define GQA_PK 4
#define GQA_STAGES 6
#define GQA_WINDOW 3
#define GQA_PACE 1

namespace gqa {

constexpr int kD = 128;
constexpr int kSk = 8192;
constexpr int kHeads = 64;
constexpr int kCtas = 2 * kHeads;
constexpr int kRows = 16;
constexpr int kTile = 128;
constexpr int kTiles = kSk / 2 / kTile;
constexpr int kUnits = 2 * kTiles;
constexpr int kUnitBytes = kTile * kD * 2;

constexpr int NW = GQA_NW;
constexpr int kConsumers = NW * 32;
constexpr int kThreads = kConsumers + 32;
constexpr int kNtPerWarp = 16 / NW;
constexpr int kKsPerWarp = kNtPerWarp / 2;
constexpr int kDtPerWarp = 16 / NW;

constexpr int PK = GQA_PK;
constexpr int kPieceBytes = PK * kD * 2;
constexpr int kPieceStride = kPieceBytes + 16;
constexpr int kPieces = kTile / PK;
constexpr int kStageBytes = kPieces * kPieceStride;
constexpr int kStages = GQA_STAGES;
constexpr int kWindow = GQA_WINDOW;
constexpr int kFirst = GQA_PACE ? (kWindow + 1 < kStages ? kWindow + 1 : kStages) : kStages;

constexpr int kOffP = kStages * kStageBytes;
constexpr int kOffXo = kOffP + 4096;
constexpr int kOffMax = kOffXo + 4096;
constexpr int kOffSum = kOffMax + kRows * NW * 4;
constexpr int kOffXml = kOffSum + kRows * NW * 4;
constexpr int kOffBar = kOffXml + kRows * 8;
constexpr int kBarFull = kOffBar;
constexpr int kBarEmpty = kBarFull + 8 * kStages;
constexpr int kBarXml = kBarEmpty + 8 * kStages;
constexpr int kBarXo = kBarXml + 8;
constexpr int kSmemBytes = kBarXo + 8;

constexpr uint32_t kProgressTotal = kCtas * kUnits;
constexpr int kPollBudget = 4096;
constexpr int kWaitLimit = 1 << 22;

__device__ unsigned int g_progress;

__device__ __forceinline__ bool elect_one() {
    uint32_t p;
    asm volatile("{ .reg .pred P; elect.sync _|P, 0xffffffff; selp.u32 %0, 1, 0, P; }" : "=r"(p));
    return p != 0;
}
__device__ __forceinline__ void mbar_init(uint32_t bar, uint32_t count) {
    asm volatile("mbarrier.init.shared::cta.b64 [%0], %1;" ::"r"(bar), "r"(count) : "memory");
}
__device__ __forceinline__ void mbar_init_fence() {
    asm volatile("fence.mbarrier_init.release.cluster;" ::: "memory");
}
__device__ __forceinline__ void mbar_expect_tx(uint32_t bar, uint32_t bytes) {
    asm volatile("mbarrier.arrive.expect_tx.shared::cta.b64 _, [%0], %1;" ::"r"(bar), "r"(bytes) : "memory");
}
__device__ __forceinline__ void mbar_arrive(uint32_t bar) {
    asm volatile("mbarrier.arrive.shared::cta.b64 _, [%0];" ::"r"(bar) : "memory");
}
__device__ __forceinline__ void mbar_wait(uint32_t bar, uint32_t parity) {
    uint32_t ok = 0;
    for (int it = 0; it < kWaitLimit; ++it) {
        asm volatile("{ .reg .pred P; mbarrier.try_wait.parity.shared::cta.b64 P, [%1], %2; selp.u32 %0, 1, 0, P; }"
                     : "=r"(ok) : "r"(bar), "r"(parity) : "memory");
        if (ok) return;
    }
    __trap();
}
__device__ __forceinline__ void mbar_wait_cluster(uint32_t bar, uint32_t parity) {
    uint32_t ok = 0;
    for (int it = 0; it < kWaitLimit; ++it) {
        asm volatile("{ .reg .pred P; mbarrier.try_wait.parity.acquire.cluster.shared::cta.b64 P, [%1], %2; selp.u32 %0, 1, 0, P; }"
                     : "=r"(ok) : "r"(bar), "r"(parity) : "memory");
        if (ok) return;
    }
    __trap();
}
__device__ __forceinline__ void bulk_load(uint32_t dst, const void* src, uint32_t bytes, uint32_t bar) {
    asm volatile("cp.async.bulk.shared::cluster.global.mbarrier::complete_tx::bytes [%0], [%1], %2, [%3];"
                 ::"r"(dst), "l"(src), "r"(bytes), "r"(bar) : "memory");
}
__device__ __forceinline__ void ldsm_x4(uint32_t (&r)[4], uint32_t addr) {
    asm volatile("ldmatrix.sync.aligned.m8n8.x4.shared.b16 {%0,%1,%2,%3}, [%4];"
                 : "=r"(r[0]), "=r"(r[1]), "=r"(r[2]), "=r"(r[3]) : "r"(addr) : "memory");
}
__device__ __forceinline__ void ldsm_x4_trans(uint32_t (&r)[4], uint32_t addr) {
    asm volatile("ldmatrix.sync.aligned.m8n8.x4.trans.shared.b16 {%0,%1,%2,%3}, [%4];"
                 : "=r"(r[0]), "=r"(r[1]), "=r"(r[2]), "=r"(r[3]) : "r"(addr) : "memory");
}
__device__ __forceinline__ void mma_bf16(float (&c)[4], const uint32_t (&a)[4], uint32_t b0, uint32_t b1) {
    asm volatile("mma.sync.aligned.m16n8k16.row.col.f32.bf16.bf16.f32 {%0,%1,%2,%3}, {%4,%5,%6,%7}, {%8,%9}, {%0,%1,%2,%3};"
                 : "+f"(c[0]), "+f"(c[1]), "+f"(c[2]), "+f"(c[3])
                 : "r"(a[0]), "r"(a[1]), "r"(a[2]), "r"(a[3]), "r"(b0), "r"(b1));
}
__device__ __forceinline__ float ex2(float x) {
    float y;
    asm("ex2.approx.ftz.f32 %0, %1;" : "=f"(y) : "f"(x));
    return y;
}
__device__ __forceinline__ uint32_t pack_bf16(float lo, float hi) {
    uint32_t r;
    asm("cvt.rn.bf16x2.f32 %0, %1, %2;" : "=r"(r) : "f"(hi), "f"(lo));
    return r;
}
__device__ __forceinline__ void consumer_sync() {
    asm volatile("bar.sync 1, %0;" ::"n"(kConsumers) : "memory");
}
__device__ __forceinline__ float4 lds128(uint32_t addr) {
    float4 v;
    asm volatile("ld.shared.v4.f32 {%0,%1,%2,%3}, [%4];" : "=f"(v.x), "=f"(v.y), "=f"(v.z), "=f"(v.w) : "r"(addr) : "memory");
    return v;
}
__device__ __forceinline__ void lds128(uint32_t (&r)[4], uint32_t addr) {
    asm volatile("ld.shared.v4.u32 {%0,%1,%2,%3}, [%4];" : "=r"(r[0]), "=r"(r[1]), "=r"(r[2]), "=r"(r[3]) : "r"(addr) : "memory");
}
__device__ __forceinline__ void sts32(uint32_t addr, float v) {
    asm volatile("st.shared.f32 [%0], %1;" ::"r"(addr), "f"(v) : "memory");
}
__device__ __forceinline__ void sts128(uint32_t addr, uint32_t a, uint32_t b, uint32_t c, uint32_t d) {
    asm volatile("st.shared.v4.u32 [%0], {%1,%2,%3,%4};" ::"r"(addr), "r"(a), "r"(b), "r"(c), "r"(d) : "memory");
}
__device__ __forceinline__ uint32_t map_to_cta(uint32_t addr, uint32_t rank) {
    uint32_t r;
    asm("mapa.shared::cluster.u32 %0, %1, %2;" : "=r"(r) : "r"(addr), "r"(rank));
    return r;
}
__device__ __forceinline__ void st_async_v2(uint32_t addr, float a, float b, uint32_t bar) {
    asm volatile("st.async.weak.shared::cluster.mbarrier::complete_tx::bytes.v2.f32 [%0], {%1,%2}, [%3];"
                 ::"r"(addr), "f"(a), "f"(b), "r"(bar) : "memory");
}
__device__ __forceinline__ void st_async_v4(uint32_t addr, float a, float b, float c, float d, uint32_t bar) {
    asm volatile("st.async.weak.shared::cluster.mbarrier::complete_tx::bytes.v4.f32 [%0], {%1,%2,%3,%4}, [%5];"
                 ::"r"(addr), "f"(a), "f"(b), "f"(c), "f"(d), "r"(bar) : "memory");
}
__device__ __forceinline__ void progress_tick() {
    asm volatile("red.relaxed.gpu.global.inc.u32 [%0], %1;" ::"l"(&g_progress), "r"(kProgressTotal - 1) : "memory");
}
template <bool kMax>
__device__ __forceinline__ float reduce_row(uint32_t addr) {
    float4 a = lds128(addr);
    float r = kMax ? fmaxf(fmaxf(a.x, a.y), fmaxf(a.z, a.w)) : (a.x + a.y) + (a.z + a.w);
    if (NW == 8) {
        float4 b = lds128(addr + 16);
        r = kMax ? fmaxf(r, fmaxf(fmaxf(b.x, b.y), fmaxf(b.z, b.w))) : r + ((b.x + b.y) + (b.z + b.w));
    }
    return r;
}
__host__ __device__ constexpr int nt_offset(int nt) {
    return (nt / PK) * 8 * kPieceStride + (nt % PK) * (kD * 2);
}

__device__ __forceinline__ void issue_unit(uint32_t smem, int stage, const char* src) {
    const uint32_t bar = smem + kBarFull + 8 * stage;
    const uint32_t dst = smem + stage * kStageBytes;
    mbar_expect_tx(bar, kUnitBytes);
#pragma unroll 8
    for (int p = 0; p < kPieces; ++p) bulk_load(dst + p * kPieceStride, src + p * kPieceBytes, kPieceBytes, bar);
}

__global__ void __cluster_dims__(2, 1, 1) __launch_bounds__(kThreads, 1)
attn_kernel(const __nv_bfloat16* __restrict__ q, const __nv_bfloat16* __restrict__ k,
            const __nv_bfloat16* __restrict__ v, __nv_bfloat16* __restrict__ out
) {
    extern __shared__ __align__(128) unsigned char smem_raw[];
    const uint32_t smem = (uint32_t)__cvta_generic_to_shared(smem_raw);
    const int warp = threadIdx.x >> 5;
    const int lane = threadIdx.x & 31;
    const int cta = blockIdx.x;
    const int head = cta >> 1;
    const uint32_t rank = cta & 1;

    if (warp == NW) {
        const char* kp = reinterpret_cast<const char*>(k) + (size_t)cta * (kTiles * kUnitBytes);
        const char* vp = reinterpret_cast<const char*>(v) + (size_t)cta * (kTiles * kUnitBytes);
        const bool leader = elect_one();
        if (leader) {
#pragma unroll 1
            for (int u = 0; u < kFirst; ++u) {
                mbar_init(smem + kBarFull + 8 * u, 1);
                mbar_init_fence();
                issue_unit(smem, u, ((u & 1) ? vp : kp) + (u >> 1) * kUnitBytes);
            }
        }
        __syncwarp();
        asm volatile("barrier.cluster.arrive.release.aligned;" ::: "memory");
        asm volatile("barrier.cluster.wait.acquire.aligned;" ::: "memory");
        if (leader) {
            int stage = kFirst % kStages;
            uint32_t parity = (kFirst / kStages) & 1;
            uint32_t seen = 0;
            int budget = kPollBudget;
#pragma unroll 1
            for (int u = kFirst; u < kUnits; ++u) {
                mbar_wait(smem + kBarEmpty + 8 * stage, parity ^ 1);
                const uint32_t need = (uint32_t)(u - kWindow) * kCtas;
                while (seen < need && budget > 0) {
                    asm volatile("ld.relaxed.gpu.global.u32 %0, [%1];" : "=r"(seen) : "l"(&g_progress) : "memory");
                    --budget;
                }
                issue_unit(smem, stage, ((u & 1) ? vp : kp) + (u >> 1) * kUnitBytes);
                if (++stage == kStages) { stage = 0; parity ^= 1; }
            }
        }
        return;
    }

    const int g = lane >> 2;
    const int t4 = lane & 3;
    if (threadIdx.x == 0) {
        for (int s = kFirst; s < kStages; ++s) mbar_init(smem + kBarFull + 8 * s, 1);
        for (int s = 0; s < kStages; ++s) mbar_init(smem + kBarEmpty + 8 * s, NW);
        mbar_init(smem + kBarXml, 1);
        mbar_init(smem + kBarXo, 1);
        mbar_init_fence();
        mbar_expect_tx(smem + kBarXml, kRows * 8);
        mbar_expect_tx(smem + kBarXo, kRows * kD * 4 / 2);
    }
    uint32_t qa[8][4];
    {
        const uint32_t* qp = reinterpret_cast<const uint32_t*>(q + (size_t)head * kRows * kD) + g * (kD / 2) + t4;
#pragma unroll
        for (int ks = 0; ks < 8; ++ks) {
            qa[ks][0] = __ldg(qp + ks * 8);
            qa[ks][1] = __ldg(qp + ks * 8 + 8 * (kD / 2));
            qa[ks][2] = __ldg(qp + ks * 8 + 4);
            qa[ks][3] = __ldg(qp + ks * 8 + 8 * (kD / 2) + 4);
        }
    }
    __syncwarp();
    asm volatile("barrier.cluster.arrive.release.aligned;" ::: "memory");
    asm volatile("barrier.cluster.wait.acquire.aligned;" ::: "memory");

    const float c = 0.08838834764831845f * 1.4426950408889634f;
    const int mi = lane >> 3;
    const uint32_t row_off = (lane & 7) * kPieceStride;
    const uint32_t k_off = row_off + mi * 16;
    const uint32_t v_off = row_off + (mi & 1) * (kD * 2) + (warp * kDtPerWarp + (mi >> 1)) * 16;
    uint32_t k_nt[kNtPerWarp];
#pragma unroll
    for (int n = 0; n < kNtPerWarp; ++n) k_nt[n] = nt_offset(warp * kNtPerWarp + n) + k_off;
    const uint32_t max_w = smem + kOffMax + (g * NW + warp) * 4;
    const uint32_t max_r = smem + kOffMax + g * NW * 4;
    const uint32_t p_w = smem + kOffP + (warp * kKsPerWarp * 32 + lane) * 16;
    const uint32_t p_r = smem + kOffP + lane * 16;

    float m0 = -INFINITY, m1 = -INFINITY, l0 = 0.f, l1 = 0.f;
    float f0 = 0.f, f1 = 0.f;
    float o[kDtPerWarp][4];
#pragma unroll
    for (int n = 0; n < kDtPerWarp; ++n) o[n][0] = o[n][1] = o[n][2] = o[n][3] = 0.f;

    int stage = 0;
    uint32_t parity = 0;
#pragma unroll 1
    for (int t = 0; t < kTiles; ++t) {
        float s[kNtPerWarp][4];
#pragma unroll
        for (int n = 0; n < kNtPerWarp; ++n) s[n][0] = s[n][1] = s[n][2] = s[n][3] = 0.f;
        mbar_wait(smem + kBarFull + 8 * stage, parity);
        if (threadIdx.x == 0) progress_tick();
        {
            const uint32_t base = smem + stage * kStageBytes;
#pragma unroll
            for (int j = 0; j < 4; ++j) {
#pragma unroll
                for (int n = 0; n < kNtPerWarp; ++n) {
                    uint32_t b[4];
                    ldsm_x4(b, base + k_nt[n] + j * 64);
                    mma_bf16(s[n], qa[2 * j], b[0], b[1]);
                    mma_bf16(s[n], qa[2 * j + 1], b[2], b[3]);
                }
            }
        }
        if (lane == 0) mbar_arrive(smem + kBarEmpty + 8 * stage);
        if (++stage == kStages) { stage = 0; parity ^= 1; }

        float mx0 = fmaxf(s[0][0], s[0][1]), mx1 = fmaxf(s[0][2], s[0][3]);
#pragma unroll
        for (int n = 1; n < kNtPerWarp; ++n) {
            mx0 = fmaxf(mx0, fmaxf(s[n][0], s[n][1]));
            mx1 = fmaxf(mx1, fmaxf(s[n][2], s[n][3]));
        }
        mx0 = fmaxf(mx0, __shfl_xor_sync(0xffffffffu, mx0, 1));
        mx1 = fmaxf(mx1, __shfl_xor_sync(0xffffffffu, mx1, 1));
        mx0 = fmaxf(mx0, __shfl_xor_sync(0xffffffffu, mx0, 2));
        mx1 = fmaxf(mx1, __shfl_xor_sync(0xffffffffu, mx1, 2));
        if (t4 == 0) {
            sts32(max_w, mx0);
            sts32(max_w + 8 * NW * 4, mx1);
        }
        consumer_sync();
        const float mn0 = fmaxf(m0, reduce_row<true>(max_r));
        const float mn1 = fmaxf(m1, reduce_row<true>(max_r + 8 * NW * 4));
        const float a0 = ex2((m0 - mn0) * c), a1 = ex2((m1 - mn1) * c);
        m0 = mn0;
        m1 = mn1;
        const float b0 = -mn0 * c, b1 = -mn1 * c;
        l0 *= a0;
        l1 *= a1;
#pragma unroll
        for (int n = 0; n < kNtPerWarp; ++n) {
            s[n][0] = ex2(fmaf(s[n][0], c, b0));
            s[n][1] = ex2(fmaf(s[n][1], c, b0));
            s[n][2] = ex2(fmaf(s[n][2], c, b1));
            s[n][3] = ex2(fmaf(s[n][3], c, b1));
            l0 += s[n][0] + s[n][1];
            l1 += s[n][2] + s[n][3];
        }
#pragma unroll
        for (int i = 0; i < kKsPerWarp; ++i)
            sts128(p_w + i * 512, pack_bf16(s[2 * i][0], s[2 * i][1]), pack_bf16(s[2 * i][2], s[2 * i][3]),
                   pack_bf16(s[2 * i + 1][0], s[2 * i + 1][1]), pack_bf16(s[2 * i + 1][2], s[2 * i + 1][3]));
        const bool last = (t == kTiles - 1);
        if (last) {
            l0 += __shfl_xor_sync(0xffffffffu, l0, 1);
            l1 += __shfl_xor_sync(0xffffffffu, l1, 1);
            l0 += __shfl_xor_sync(0xffffffffu, l0, 2);
            l1 += __shfl_xor_sync(0xffffffffu, l1, 2);
            if (t4 == 0) {
                sts32(max_w + (kOffSum - kOffMax), l0);
                sts32(max_w + (kOffSum - kOffMax) + 8 * NW * 4, l1);
            }
        }
#pragma unroll
        for (int n = 0; n < kDtPerWarp; ++n) {
            o[n][0] *= a0; o[n][1] *= a0; o[n][2] *= a1; o[n][3] *= a1;
        }
        consumer_sync();
        uint32_t pa[8][4];
#pragma unroll
        for (int ks = 0; ks < 8; ++ks) lds128(pa[ks], p_r + ks * 512);

        if (last) {
            l0 = reduce_row<false>(max_r + (kOffSum - kOffMax));
            l1 = reduce_row<false>(max_r + (kOffSum - kOffMax) + 8 * NW * 4);
            if (warp == 0 && t4 == 0) {
                const uint32_t dst = map_to_cta(smem + kOffXml + g * 8, rank ^ 1);
                const uint32_t bar = map_to_cta(smem + kBarXml, rank ^ 1);
                st_async_v2(dst, m0, l0, bar);
                st_async_v2(dst + 64, m1, l1, bar);
            }
            mbar_wait_cluster(smem + kBarXml, 0);
            float pm0, pl0, pm1, pl1;
            asm volatile("ld.shared.v2.f32 {%0,%1}, [%2];" : "=f"(pm0), "=f"(pl0) : "r"(smem + kOffXml + g * 8) : "memory");
            asm volatile("ld.shared.v2.f32 {%0,%1}, [%2];" : "=f"(pm1), "=f"(pl1) : "r"(smem + kOffXml + g * 8 + 64) : "memory");
            const float mf0 = fmaxf(m0, pm0), mf1 = fmaxf(m1, pm1);
            const float e0 = ex2((m0 - mf0) * c), e1 = ex2((m1 - mf1) * c);
            f0 = e0 / (l0 * e0 + pl0 * ex2((pm0 - mf0) * c));
            f1 = e1 / (l1 * e1 + pl1 * ex2((pm1 - mf1) * c));
        }

        mbar_wait(smem + kBarFull + 8 * stage, parity);
        if (threadIdx.x == 0) progress_tick();
        {
            const uint32_t base = smem + stage * kStageBytes + v_off;
#pragma unroll
            for (int ks = 0; ks < 8; ++ks) {
#pragma unroll
                for (int n = 0; n < kDtPerWarp; n += 2) {
                    uint32_t b[4];
                    ldsm_x4_trans(b, base + nt_offset(2 * ks) + n * 16);
                    mma_bf16(o[n], pa[ks], b[0], b[1]);
                    mma_bf16(o[n + 1], pa[ks], b[2], b[3]);
                }
            }
        }
        if (lane == 0) mbar_arrive(smem + kBarEmpty + 8 * stage);
        if (++stage == kStages) { stage = 0; parity ^= 1; }
    }

    float keep[kDtPerWarp][2];
    {
        const uint32_t dst = map_to_cta(smem + kOffXo + threadIdx.x * 16, rank ^ 1);
        const uint32_t bar = map_to_cta(smem + kBarXo, rank ^ 1);
        const float fs = rank ? f0 : f1, fk = rank ? f1 : f0;
#pragma unroll
        for (int n = 0; n < kDtPerWarp; n += 2) {
            st_async_v4(dst + (n / 2) * kConsumers * 16,
                        (rank ? o[n][0] : o[n][2]) * fs, (rank ? o[n][1] : o[n][3]) * fs,
                        (rank ? o[n + 1][0] : o[n + 1][2]) * fs, (rank ? o[n + 1][1] : o[n + 1][3]) * fs, bar);
        }
#pragma unroll
        for (int n = 0; n < kDtPerWarp; ++n) {
            keep[n][0] = (rank ? o[n][2] : o[n][0]) * fk;
            keep[n][1] = (rank ? o[n][3] : o[n][1]) * fk;
        }
    }
    uint32_t* op = reinterpret_cast<uint32_t*>(out + ((size_t)head * kRows + rank * 8 + g) * kD + warp * kDtPerWarp * 8) + t4;
    mbar_wait_cluster(smem + kBarXo, 0);
#pragma unroll
    for (int n = 0; n < kDtPerWarp; n += 2) {
        const float4 x = lds128(smem + kOffXo + threadIdx.x * 16 + (n / 2) * kConsumers * 16);
        op[n * 4] = pack_bf16(keep[n][0] + x.x, keep[n][1] + x.y);
        op[n * 4 + 4] = pack_bf16(keep[n + 1][0] + x.z, keep[n + 1][1] + x.w);
    }
}

}

extern "C" void kernel_launch(void* const* d_in, const int* in_sizes, int n_in, void* d_out, int out_size) {
    (void)in_sizes; (void)n_in; (void)out_size;
    cudaFuncSetAttribute(gqa::attn_kernel, cudaFuncAttributeMaxDynamicSharedMemorySize, gqa::kSmemBytes);
    gqa::attn_kernel<<<gqa::kCtas, gqa::kThreads, gqa::kSmemBytes>>>(
        (const __nv_bfloat16*)d_in[0], (const __nv_bfloat16*)d_in[1], (const __nv_bfloat16*)d_in[2],
        (__nv_bfloat16*)d_out);
}
```

```cpp
#include <cuda.h>
#include <cuda_runtime.h>
#include <cuda_bf16.h>
#include <stdint.h>

#define GQA_NW 8
#define GQA_STAGES 6
#define GQA_W0 768
#define GQA_W1 256
#define GQA_U0 44
#define GQA_MON 0
#define GQA_ILV 0
#define GQA_PDEFER 1
#define GQA_FIRSTWARP 1
#define GQA_LIGHT_ACQ 1
#define GQA_PACE 1

#define GQA_NS gqa

namespace GQA_NS {

constexpr int kD = 128;
constexpr int kSk = 8192;
constexpr int kHeads = 64;
constexpr int kCtas = 2 * kHeads;
constexpr int kRows = 16;
constexpr int kTile = 128;
constexpr int kTiles = kSk / 2 / kTile;
constexpr int kUnits = 2 * kTiles;
constexpr int kUnitBytes = kTile * kD * 2;
constexpr int G = 4;
constexpr int kSupers = kTiles / G;

constexpr int NW = GQA_NW;
constexpr int kConsumers = NW * 32;
constexpr int kThreads = kConsumers + 32 + (GQA_MON ? 32 : 0);
constexpr int kNtPerWarp = 16 / NW;
constexpr int kKsPerWarp = kNtPerWarp / 2;
constexpr int kDtPerWarp = 16 / NW;

constexpr int kBoxKeys = 32;
constexpr int kBoxBytes = kBoxKeys * kD * 2;
constexpr int kBoxes = kTile / kBoxKeys;
constexpr int kGroupBytes = 8 * kD * 2;
constexpr int kStageBytes = kUnitBytes;
constexpr int kStages = GQA_STAGES;

constexpr int kW0 = GQA_W0, kW1 = GQA_W1, kU0 = GQA_U0;
constexpr int kFirst = GQA_PACE ? (kW0 / kCtas + 1 < kStages ? kW0 / kCtas + 1 : kStages) : kStages;

constexpr int kQStride = kD * 2 + 16;
constexpr int kOffP = kStages * kStageBytes;
constexpr int kOffXo = kOffP + G * 4096;
constexpr int kOffQ = kOffXo + 4096;
constexpr int kOffMax = kOffQ + kRows * kQStride;
constexpr int kOffSum = kOffMax + kRows * NW * 4;
constexpr int kOffXml = kOffSum + kRows * NW * 4;
constexpr int kBarFull = kOffXml + kRows * 8;
constexpr int kBarEmpty = kBarFull + 8 * kStages * kBoxes;
constexpr int kBarXml = kBarEmpty + 8 * kStages;
constexpr int kBarXo = kBarXml + 8;
constexpr int kBarQ = kBarXo + 8 * NW;
constexpr int kSmemBytes = kBarQ + 8 + 1024;

constexpr uint32_t kProgressTotal = kCtas * (kUnits - 1);
constexpr int kPollBudget = 4096;
constexpr int kWaitLimit = 1 << 22;

__device__ unsigned int g_progress;

__device__ __forceinline__ bool elect_one() {
    uint32_t p;
    asm volatile("{ .reg .pred P; elect.sync _|P, 0xffffffff; selp.u32 %0, 1, 0, P; }" : "=r"(p));
    return p != 0;
}
__device__ __forceinline__ void mbar_init(uint32_t bar, uint32_t count) {
    asm volatile("mbarrier.init.shared::cta.b64 [%0], %1;" ::"r"(bar), "r"(count) : "memory");
}
__device__ __forceinline__ void mbar_init_fence() {
    asm volatile("fence.mbarrier_init.release.cluster;" ::: "memory");
}
__device__ __forceinline__ void mbar_expect_tx(uint32_t bar, uint32_t bytes) {
    asm volatile("mbarrier.arrive.expect_tx.shared::cta.b64 _, [%0], %1;" ::"r"(bar), "r"(bytes) : "memory");
}
__device__ __forceinline__ void mbar_arrive(uint32_t bar) {
    asm volatile("mbarrier.arrive.shared::cta.b64 _, [%0];" ::"r"(bar) : "memory");
}
__device__ __forceinline__ void mbar_wait(uint32_t bar, uint32_t parity) {
    asm volatile(
        "{\n"
        ".reg .pred P, Q;\n"
        ".reg .u32 n;\n"
        "mov.u32 n, 0;\n"
        "WAIT_LOOP:\n"
        "mbarrier.try_wait.parity.shared::cta.b64 P, [%0], %1;\n"
        "@P bra WAIT_DONE;\n"
        "add.u32 n, n, 1;\n"
        "setp.lt.u32 Q, n, %2;\n"
        "@Q bra WAIT_LOOP;\n"
        "trap;\n"
        "WAIT_DONE:\n"
        "}\n" ::"r"(bar), "r"(parity), "n"(kWaitLimit) : "memory");
}
__device__ __forceinline__ bool mbar_test(uint32_t bar, uint32_t parity) {
    uint32_t ok;
    asm volatile("{ .reg .pred P; mbarrier.test_wait.parity.shared::cta.b64 P, [%1], %2; selp.u32 %0, 1, 0, P; }"
                 : "=r"(ok) : "r"(bar), "r"(parity) : "memory");
    return ok != 0;
}
__device__ __forceinline__ void mbar_wait_cluster(uint32_t bar, uint32_t parity) {
    asm volatile(
        "{\n"
        ".reg .pred P, Q;\n"
        ".reg .u32 n;\n"
        "mov.u32 n, 0;\n"
        "WAIT_LOOP:\n"
        "mbarrier.try_wait.parity.relaxed.cluster.shared::cta.b64 P, [%0], %1;\n"
        "@P bra WAIT_DONE;\n"
        "add.u32 n, n, 1;\n"
        "setp.lt.u32 Q, n, %2;\n"
        "@Q bra WAIT_LOOP;\n"
        "trap;\n"
        "WAIT_DONE:\n"
        "fence.acquire.sync_restrict::shared::cluster.cluster;\n"
        "}\n" ::"r"(bar), "r"(parity), "n"(kWaitLimit) : "memory");
}
__device__ __forceinline__ void tma_load_box(uint32_t dst, const CUtensorMap* map, int group, uint32_t bar) {
    asm volatile("cp.async.bulk.tensor.4d.shared::cluster.global.mbarrier::complete_tx::bytes [%0], [%1, {%3, %3, %3, %4}], [%2];"
                 ::"r"(dst), "l"(map), "r"(bar), "r"(0), "r"(group) : "memory");
}
__device__ __forceinline__ void bulk_load(uint32_t dst, const void* src, uint32_t bytes, uint32_t bar) {
    asm volatile("cp.async.bulk.shared::cluster.global.mbarrier::complete_tx::bytes [%0], [%1], %2, [%3];"
                 ::"r"(dst), "l"(src), "r"(bytes), "r"(bar) : "memory");
}
__device__ __forceinline__ void ldsm_x4(uint32_t (&r)[4], uint32_t addr) {
    asm volatile("ldmatrix.sync.aligned.m8n8.x4.shared.b16 {%0,%1,%2,%3}, [%4];"
                 : "=r"(r[0]), "=r"(r[1]), "=r"(r[2]), "=r"(r[3]) : "r"(addr) : "memory");
}
__device__ __forceinline__ void ldsm_x4_trans(uint32_t (&r)[4], uint32_t addr) {
    asm volatile("ldmatrix.sync.aligned.m8n8.x4.trans.shared.b16 {%0,%1,%2,%3}, [%4];"
                 : "=r"(r[0]), "=r"(r[1]), "=r"(r[2]), "=r"(r[3]) : "r"(addr) : "memory");
}
__device__ __forceinline__ void mma_bf16(float (&c)[4], const uint32_t (&a)[4], uint32_t b0, uint32_t b1) {
    asm volatile("mma.sync.aligned.m16n8k16.row.col.f32.bf16.bf16.f32 {%0,%1,%2,%3}, {%4,%5,%6,%7}, {%8,%9}, {%0,%1,%2,%3};"
                 : "+f"(c[0]), "+f"(c[1]), "+f"(c[2]), "+f"(c[3])
                 : "r"(a[0]), "r"(a[1]), "r"(a[2]), "r"(a[3]), "r"(b0), "r"(b1));
}
__device__ __forceinline__ float ex2(float x) {
    float y;
    asm("ex2.approx.ftz.f32 %0, %1;" : "=f"(y) : "f"(x));
    return y;
}
__device__ __forceinline__ uint32_t pack_bf16(float lo, float hi) {
    uint32_t r;
    asm("cvt.rn.bf16x2.f32 %0, %1, %2;" : "=r"(r) : "f"(hi), "f"(lo));
    return r;
}
__device__ __forceinline__ void consumer_sync() {
    asm volatile("bar.sync 1, %0;" ::"n"(kConsumers) : "memory");
}
__device__ __forceinline__ float4 lds128(uint32_t addr) {
    float4 v;
    asm volatile("ld.shared.v4.f32 {%0,%1,%2,%3}, [%4];" : "=f"(v.x), "=f"(v.y), "=f"(v.z), "=f"(v.w) : "r"(addr) : "memory");
    return v;
}
__device__ __forceinline__ void lds128(uint32_t (&r)[4], uint32_t addr) {
    asm volatile("ld.shared.v4.u32 {%0,%1,%2,%3}, [%4];" : "=r"(r[0]), "=r"(r[1]), "=r"(r[2]), "=r"(r[3]) : "r"(addr) : "memory");
}
__device__ __forceinline__ void sts32(uint32_t addr, float v) {
    asm volatile("st.shared.f32 [%0], %1;" ::"r"(addr), "f"(v) : "memory");
}
__device__ __forceinline__ void sts128(uint32_t addr, uint32_t a, uint32_t b, uint32_t c, uint32_t d) {
    asm volatile("st.shared.v4.u32 [%0], {%1,%2,%3,%4};" ::"r"(addr), "r"(a), "r"(b), "r"(c), "r"(d) : "memory");
}
__device__ __forceinline__ void stg32(uint64_t addr, uint32_t v) {
    asm volatile("st.global.u32 [%0], %1;" ::"l"(addr), "r"(v) : "memory");
}
__device__ __forceinline__ uint32_t map_to_cta(uint32_t addr, uint32_t rank) {
    uint32_t r;
    asm("mapa.shared::cluster.u32 %0, %1, %2;" : "=r"(r) : "r"(addr), "r"(rank));
    return r;
}
__device__ __forceinline__ void st_async_v2(uint32_t addr, float a, float b, uint32_t bar) {
    asm volatile("st.async.weak.shared::cluster.mbarrier::complete_tx::bytes.v2.f32 [%0], {%1,%2}, [%3];"
                 ::"r"(addr), "f"(a), "f"(b), "r"(bar) : "memory");
}
__device__ __forceinline__ void st_async_v4(uint32_t addr, float a, float b, float c, float d, uint32_t bar) {
    asm volatile("st.async.weak.shared::cluster.mbarrier::complete_tx::bytes.v4.f32 [%0], {%1,%2,%3,%4}, [%5];"
                 ::"r"(addr), "f"(a), "f"(b), "f"(c), "f"(d), "r"(bar) : "memory");
}
__device__ __forceinline__ void progress_tick() {
    asm volatile("red.relaxed.gpu.global.inc.u32 [%0], %1;" ::"l"(&g_progress), "r"(kProgressTotal - 1) : "memory");
}
template <bool kMax>
__device__ __forceinline__ float reduce_row(uint32_t addr) {
    float4 a = lds128(addr);
    float r = kMax ? fmaxf(fmaxf(a.x, a.y), fmaxf(a.z, a.w)) : (a.x + a.y) + (a.z + a.w);
    if (NW == 8) {
        float4 b = lds128(addr + 16);
        r = kMax ? fmaxf(r, fmaxf(fmaxf(b.x, b.y), fmaxf(b.z, b.w))) : r + ((b.x + b.y) + (b.z + b.w));
    }
    return r;
}
__device__ __forceinline__ void issue_unit(uint32_t smem, int stage, int u, int group0,
                                           const CUtensorMap* kmap, const CUtensorMap* vmap) {
    const bool is_k = (u % (2 * G)) < G;
    const int tile = (u / (2 * G)) * G + u % G;
    const CUtensorMap* map = is_k ? kmap : vmap;
    const int group = group0 + (GQA_ILV == 1 ? 2 * tile : GQA_ILV == 2 ? tile + (tile / G) * G : tile) * (kTile / 8);
    const uint32_t bar = smem + kBarFull + 8 * kBoxes * stage;
    const uint32_t dst = smem + stage * kStageBytes;
#pragma unroll
    for (int b = 0; b < kBoxes; ++b) {
        mbar_expect_tx(bar + 8 * b, kBoxBytes);
        tma_load_box(dst + b * kBoxBytes, map, group + b * (kBoxKeys / 8), bar + 8 * b);
    }
}

#define GQA_T(i)

__global__ void __cluster_dims__(2, 1, 1) __launch_bounds__(kThreads, 1)
attn_kernel(const __nv_bfloat16* __restrict__ q, __nv_bfloat16* __restrict__ out,
            const __grid_constant__ CUtensorMap kmap, const __grid_constant__ CUtensorMap vmap) {
    extern __shared__ __align__(128) unsigned char smem_raw[];
    const uint32_t smem = ((uint32_t)__cvta_generic_to_shared(smem_raw) + 1023u) & ~1023u;
    GQA_T(0);
    const int warp = threadIdx.x >> 5;
    const int lane = threadIdx.x & 31;
    const int cta = blockIdx.x;
    const int head = cta >> 1;
    const uint32_t rank = cta & 1;

    const int group0 = GQA_ILV == 0 ? cta * (kTiles * kTile / 8)
                                    : head * (kSk / 8) + rank * (GQA_ILV == 1 ? 1 : G) * (kTile / 8);
    if (warp == GQA_FIRSTWARP && elect_one()) {
        mbar_init(smem + kBarFull, 1);
        mbar_init_fence();
        mbar_expect_tx(smem + kBarFull, kBoxBytes);
        tma_load_box(smem, &kmap, group0, smem + kBarFull);
#pragma unroll
        for (int b = 1; b < kBoxes; ++b) mbar_init(smem + kBarFull + 8 * b, 1);
        mbar_init_fence();
#pragma unroll
        for (int b = 1; b < kBoxes; ++b) {
            mbar_expect_tx(smem + kBarFull + 8 * b, kBoxBytes);
            tma_load_box(smem + b * kBoxBytes, &kmap, group0 + b * (kBoxKeys / 8), smem + kBarFull + 8 * b);
        }
    }

    if (warp == NW) {
        const bool leader = elect_one();
        if (leader) {
            mbar_init(smem + kBarQ, 1);
            mbar_init_fence();
            mbar_expect_tx(smem + kBarQ, kRows * kD * 2);
#pragma unroll 4
            for (int r = 0; r < kRows; ++r)
                bulk_load(smem + kOffQ + r * kQStride, q + ((size_t)head * kRows + r) * kD, kD * 2, smem + kBarQ);
#pragma unroll 1
            for (int u = 1; u < kFirst; ++u) {
#pragma unroll
                for (int b = 0; b < kBoxes; ++b) mbar_init(smem + kBarFull + 8 * (kBoxes * u + b), 1);
                mbar_init_fence();
                issue_unit(smem, u, u, group0, &kmap, &vmap);
            }
        }
        __syncwarp();
        asm volatile("barrier.cluster.arrive.relaxed.aligned;" ::: "memory");
        asm volatile("barrier.cluster.wait.acquire.aligned;" ::: "memory");
        if (leader) {
            int stage = kFirst % kStages;
            uint32_t parity = (kFirst / kStages) & 1;
            int seen = 0;
            int budget = kPollBudget;
#pragma unroll 1
            for (int u = kFirst; u < kUnits; ++u) {
                mbar_wait(smem + kBarEmpty + 8 * stage, parity ^ 1);
                const int window = u <= kU0 ? kW0 : kW0 - (kW0 - kW1) * (u - kU0) / (kUnits - 1 - kU0);
                const int need = u * kCtas - window;
                while (seen < need && budget > 0) {
                    asm volatile("ld.relaxed.gpu.global.u32 %0, [%1];" : "=r"(seen) : "l"(&g_progress) : "memory");
                    --budget;
                }
                issue_unit(smem, stage, u, group0, &kmap, &vmap);
                if (++stage == kStages) { stage = 0; parity ^= 1; }
            }
        }
        return;
    }

    const int g = lane >> 2;
    const int t4 = lane & 3;
    if (threadIdx.x == 0) {
        for (int i = kFirst * kBoxes; i < kStages * kBoxes; ++i) mbar_init(smem + kBarFull + 8 * i, 1);
        for (int s = 0; s < kStages; ++s) mbar_init(smem + kBarEmpty + 8 * s, NW + (GQA_MON ? 1 : 0));
        mbar_init(smem + kBarXml, 1);
        for (int w = 0; w < NW; ++w) mbar_init(smem + kBarXo + 8 * w, 1);
        mbar_init_fence();
        mbar_expect_tx(smem + kBarXml, kRows * 8);
        for (int w = 0; w < NW; ++w) mbar_expect_tx(smem + kBarXo + 8 * w, kRows * kD * 4 / 2 / NW);
    }
    __syncwarp();
    asm volatile("barrier.cluster.arrive.relaxed.aligned;" ::: "memory");
    asm volatile("barrier.cluster.wait.acquire.aligned;" ::: "memory");

    const float c = 0.08838834764831845f * 1.4426950408889634f;
    const int mi = lane >> 3;
    const int r8 = lane & 7;
    const uint32_t k_off = warp * kNtPerWarp * kGroupBytes + r8 * 128 + ((mi ^ r8) << 4);
    const uint32_t k_bar = kBarFull + 8 * (warp * kNtPerWarp * 8 / kBoxKeys);
    const int vc = warp * kDtPerWarp + (mi >> 1);
    const uint32_t v_off = (mi & 1) * kGroupBytes + (vc >> 3) * 1024 + r8 * 128 + (((vc & 7) ^ r8) << 4);
    const uint32_t max_w = smem + kOffMax + (g * NW + warp) * 4;
    const uint32_t max_r = smem + kOffMax + g * NW * 4;
    const uint32_t p_w = smem + kOffP + (warp * kKsPerWarp * 32 + lane) * 16;
    const uint32_t p_r = smem + kOffP + lane * 16;
    const bool ticker = !GQA_MON && threadIdx.x == kConsumers - 32;

    const uint32_t q_r = smem + kOffQ + ((mi & 1) * 8 + r8) * kQStride + (mi >> 1) * 16;
    mbar_wait(smem + kBarQ, 0);

    uint32_t xo = smem + kOffXo + threadIdx.x * 16;
    uint32_t xo_bar = smem + kBarXo + 8 * warp;
    uint32_t xo_peer = map_to_cta(xo, rank ^ 1);
    uint32_t xo_bar_peer = map_to_cta(xo_bar, rank ^ 1);
    uint64_t op = __cvta_generic_to_global(out + ((size_t)head * kRows + rank * 8 + g) * kD + warp * kDtPerWarp * 8 + t4 * 2);
    asm volatile("" : "+l"(op), "+r"(xo), "+r"(xo_bar), "+r"(xo_peer), "+r"(xo_bar_peer));

    float m0 = -INFINITY, m1 = -INFINITY, l0 = 0.f, l1 = 0.f;
    float f_send = 0.f, f_keep = 0.f;
    float o[2][kDtPerWarp][4];
#pragma unroll
    for (int h = 0; h < 2; ++h)
#pragma unroll
        for (int n = 0; n < kDtPerWarp; ++n) o[h][n][0] = o[h][n][1] = o[h][n][2] = o[h][n][3] = 0.f;

    int stage = 0;
    uint32_t parity = 0;
#pragma unroll 1
    for (int st = 0; st < kSupers; ++st) {
        const bool last = st == kSupers - 1;

        uint32_t qa[8][4];
#pragma unroll
        for (int ks = 0; ks < 8; ++ks) ldsm_x4(qa[ks], q_r + ks * 32);
        float s[G][kNtPerWarp][4];
#pragma unroll
        for (int i = 0; i < G; ++i) {
#pragma unroll
            for (int n = 0; n < kNtPerWarp; ++n) s[i][n][0] = s[i][n][1] = s[i][n][2] = s[i][n][3] = 0.f;
            mbar_wait(smem + k_bar + 8 * kBoxes * stage, parity);
            if (st == 0 && i == 0) GQA_T(1);
            if (last && i == G - 1) GQA_T(2);
            if (ticker) progress_tick();
            const uint32_t base = smem + stage * kStageBytes;
#pragma unroll
            for (int j = 0; j < 4; ++j) {
                uint32_t b[kNtPerWarp][4];
#pragma unroll
                for (int n = 0; n < kNtPerWarp; ++n)
                    ldsm_x4(b[n], base + (k_off ^ ((j & 1) * 64)) + n * kGroupBytes + (j >> 1) * 1024);
#pragma unroll
                for (int n = 0; n < kNtPerWarp; ++n) mma_bf16(s[i][n], qa[2 * j], b[n][0], b[n][1]);
#pragma unroll
                for (int n = 0; n < kNtPerWarp; ++n) mma_bf16(s[i][n], qa[2 * j + 1], b[n][2], b[n][3]);
            }
            if (lane == 0) mbar_arrive(smem + kBarEmpty + 8 * stage);
            if (++stage == kStages) { stage = 0; parity ^= 1; }
        }

        float mx0 = m0, mx1 = m1;
#pragma unroll
        for (int i = 0; i < G; ++i)
#pragma unroll
            for (int n = 0; n < kNtPerWarp; ++n) {
                mx0 = fmaxf(mx0, fmaxf(s[i][n][0], s[i][n][1]));
                mx1 = fmaxf(mx1, fmaxf(s[i][n][2], s[i][n][3]));
            }
        mx0 = fmaxf(mx0, __shfl_xor_sync(0xffffffffu, mx0, 1));
        mx1 = fmaxf(mx1, __shfl_xor_sync(0xffffffffu, mx1, 1));
        mx0 = fmaxf(mx0, __shfl_xor_sync(0xffffffffu, mx0, 2));
        mx1 = fmaxf(mx1, __shfl_xor_sync(0xffffffffu, mx1, 2));
        if (t4 == 0) {
            sts32(max_w, mx0);
            sts32(max_w + 8 * NW * 4, mx1);
        }
        consumer_sync();
        const float mn0 = reduce_row<true>(max_r);
        const float mn1 = reduce_row<true>(max_r + 8 * NW * 4);
        const float a0 = ex2((m0 - mn0) * c), a1 = ex2((m1 - mn1) * c);
        m0 = mn0;
        m1 = mn1;
        const float b0 = -mn0 * c, b1 = -mn1 * c;
        l0 *= a0;
        l1 *= a1;
#pragma unroll
        for (int i = 0; i < G; ++i) {
#pragma unroll
            for (int n = 0; n < kNtPerWarp; ++n) {
                s[i][n][0] = ex2(fmaf(s[i][n][0], c, b0));
                s[i][n][1] = ex2(fmaf(s[i][n][1], c, b0));
                s[i][n][2] = ex2(fmaf(s[i][n][2], c, b1));
                s[i][n][3] = ex2(fmaf(s[i][n][3], c, b1));
                l0 += s[i][n][0] + s[i][n][1];
                l1 += s[i][n][2] + s[i][n][3];
            }
#pragma unroll
            for (int x = 0; x < kKsPerWarp; ++x)
                sts128(p_w + i * 4096 + x * 512,
                       pack_bf16(s[i][2 * x][0], s[i][2 * x][1]), pack_bf16(s[i][2 * x][2], s[i][2 * x][3]),
                       pack_bf16(s[i][2 * x + 1][0], s[i][2 * x + 1][1]), pack_bf16(s[i][2 * x + 1][2], s[i][2 * x + 1][3]));
        }
        if (last) {
            l0 += __shfl_xor_sync(0xffffffffu, l0, 1);
            l1 += __shfl_xor_sync(0xffffffffu, l1, 1);
            l0 += __shfl_xor_sync(0xffffffffu, l0, 2);
            l1 += __shfl_xor_sync(0xffffffffu, l1, 2);
            if (t4 == 0) {
                sts32(max_w + (kOffSum - kOffMax), l0);
                sts32(max_w + (kOffSum - kOffMax) + 8 * NW * 4, l1);
            }
        }
#pragma unroll
        for (int h = 0; h < 2; ++h)
#pragma unroll
            for (int n = 0; n < kDtPerWarp; ++n) {
                o[h][n][0] *= a0; o[h][n][1] *= a0; o[h][n][2] *= a1; o[h][n][3] *= a1;
            }
        consumer_sync();
        uint32_t pa[G - 1][8][4];
#pragma unroll
        for (int i = 0; i < (GQA_PDEFER ? 1 : G - 1); ++i)
#pragma unroll
            for (int ks = 0; ks < 8; ++ks) lds128(pa[i][ks], p_r + i * 4096 + ks * 512);

        if (last) {
            l0 = reduce_row<false>(max_r + (kOffSum - kOffMax));
            l1 = reduce_row<false>(max_r + (kOffSum - kOffMax) + 8 * NW * 4);
            if (warp == 0 && t4 == 0) {
                const uint32_t dst = map_to_cta(smem + kOffXml + g * 8, rank ^ 1);
                const uint32_t bar = map_to_cta(smem + kBarXml, rank ^ 1);
                st_async_v2(dst, m0, l0, bar);
                st_async_v2(dst + 64, m1, l1, bar);
            }
            mbar_wait_cluster(smem + kBarXml, 0);
            float pm0, pl0, pm1, pl1;
            asm volatile("ld.shared.v2.f32 {%0,%1}, [%2];" : "=f"(pm0), "=f"(pl0) : "r"(smem + kOffXml + g * 8) : "memory");
            asm volatile("ld.shared.v2.f32 {%0,%1}, [%2];" : "=f"(pm1), "=f"(pl1) : "r"(smem + kOffXml + g * 8 + 64) : "memory");
            const float mf0 = fmaxf(m0, pm0), mf1 = fmaxf(m1, pm1);
            const float e0 = ex2((m0 - mf0) * c), e1 = ex2((m1 - mf1) * c);
            const float f0 = e0 / (l0 * e0 + pl0 * ex2((pm0 - mf0) * c));
            const float f1 = e1 / (l1 * e1 + pl1 * ex2((pm1 - mf1) * c));
            f_send = rank ? f0 : f1;
            f_keep = rank ? f1 : f0;
            GQA_T(3);
        }

        uint32_t vb[2][2][kDtPerWarp / 2][4];
        int prev_stage = stage;
        bool landed = false;
#pragma unroll
        for (int x = 0; x <= G * kBoxes; ++x) {
            const int bx = x % kBoxes;
            if (GQA_PDEFER && x == kBoxes) {
#pragma unroll
                for (int i = 1; i < G - 1; ++i)
#pragma unroll
                    for (int ks = 0; ks < 8; ++ks) lds128(pa[i][ks], p_r + i * 4096 + ks * 512);
            }
            if (x < G * kBoxes) {
                if (!landed) mbar_wait(smem + kBarFull + 8 * (kBoxes * stage + bx), parity);
                __syncwarp();
                if (last && x == 2 * kBoxes) GQA_T(9);
                if (last && x == 3 * kBoxes) GQA_T(10);
                if (last && x == G * kBoxes - 1) GQA_T(4);
                const uint32_t base = smem + stage * kStageBytes + bx * kBoxBytes;
                if (bx == kBoxes - 1) {
                    prev_stage = stage;
                    if (++stage == kStages) { stage = 0; parity ^= 1; }
                }
                if (x + 1 < G * kBoxes) landed = mbar_test(smem + kBarFull + 8 * (kBoxes * stage + (bx + 1) % kBoxes), parity);
#pragma unroll
                for (int h = 0; h < 2; ++h)
#pragma unroll
                    for (int n = 0; n < kDtPerWarp; n += 2)
                        ldsm_x4_trans(vb[x & 1][h][n / 2], base + (v_off ^ (n * 16)) + h * 2 * kGroupBytes);
            }
            if (x > 0) {
                const int y = x - 1, i = y / kBoxes, by = y % kBoxes;
#pragma unroll
                for (int h = 0; h < 2; ++h)
#pragma unroll
                    for (int n = 0; n < kDtPerWarp; n += 2) {
                        mma_bf16(o[h][n], pa[i % (G - 1)][2 * by + h], vb[y & 1][h][n / 2][0], vb[y & 1][h][n / 2][1]);
                        mma_bf16(o[h][n + 1], pa[i % (G - 1)][2 * by + h], vb[y & 1][h][n / 2][2], vb[y & 1][h][n / 2][3]);
                    }
                if (by == kBoxes - 1) {
                    if (lane == 0) mbar_arrive(smem + kBarEmpty + 8 * prev_stage);
                    if (i == 0) {
#pragma unroll
                        for (int ks = 0; ks < 8; ++ks) lds128(pa[0][ks], p_r + (G - 1) * 4096 + ks * 512);
                    }
                }
            }
            if (x < G * kBoxes && bx == kBoxes - 1 && ticker && !(last && x == G * kBoxes - 1)) progress_tick();
        }
    }

    GQA_T(5);
    {
        float keep[kDtPerWarp][2], send[kDtPerWarp][2];
#pragma unroll
        for (int n = 0; n < kDtPerWarp; ++n) {
            const float x0 = o[0][n][0] + o[1][n][0], x1 = o[0][n][1] + o[1][n][1];
            const float x2 = o[0][n][2] + o[1][n][2], x3 = o[0][n][3] + o[1][n][3];
            send[n][0] = (rank ? x0 : x2) * f_send;
            send[n][1] = (rank ? x1 : x3) * f_send;
            keep[n][0] = rank ? x2 : x0;
            keep[n][1] = rank ? x3 : x1;
        }
#pragma unroll
        for (int n = 0; n < kDtPerWarp; n += 2)
            st_async_v4(xo_peer + (n / 2) * kConsumers * 16, send[n][0], send[n][1], send[n + 1][0], send[n + 1][1], xo_bar_peer);
        GQA_T(6);
        mbar_wait_cluster(xo_bar, 0);
        GQA_T(7);
#pragma unroll
        for (int n = 0; n < kDtPerWarp; n += 2) {
            const float4 x = lds128(xo + (n / 2) * kConsumers * 16);
            stg32(op + n * 16, pack_bf16(fmaf(keep[n][0], f_keep, x.x), fmaf(keep[n][1], f_keep, x.y)));
            stg32(op + n * 16 + 16, pack_bf16(fmaf(keep[n + 1][0], f_keep, x.z), fmaf(keep[n + 1][1], f_keep, x.w)));
        }
    }
}

typedef CUresult (*EncodeTiledFn)(CUtensorMap*, CUtensorMapDataType, cuuint32_t, void*, const cuuint64_t*,
                                  const cuuint64_t*, const cuuint32_t*, const cuuint32_t*, CUtensorMapInterleave,
                                  CUtensorMapSwizzle, CUtensorMapL2promotion, CUtensorMapFloatOOBfill);

inline CUtensorMap make_map(const void* ptr) {
    static EncodeTiledFn encode = nullptr;
    if (!encode) {
        cudaDriverEntryPointQueryResult status;
        cudaGetDriverEntryPoint("cuTensorMapEncodeTiled", (void**)&encode, cudaEnableDefault, &status);
    }
    CUtensorMap map;
    const cuuint64_t dims[4] = {64, 8, 2, (cuuint64_t)kHeads * kSk / 8};
    const cuuint64_t strides[3] = {kD * 2, 128, kGroupBytes};
    const cuuint32_t box[4] = {64, 8, 2, kBoxKeys / 8};
    const cuuint32_t estr[4] = {1, 1, 1, 1};
    encode(&map, CU_TENSOR_MAP_DATA_TYPE_BFLOAT16, 4, const_cast<void*>(ptr), dims, strides, box, estr,
           CU_TENSOR_MAP_INTERLEAVE_NONE, CU_TENSOR_MAP_SWIZZLE_128B, CU_TENSOR_MAP_L2_PROMOTION_NONE,
           CU_TENSOR_MAP_FLOAT_OOB_FILL_NONE);
    return map;
}

}

extern "C" void kernel_launch(void* const* d_in, const int* in_sizes, int n_in, void* d_out, int out_size) {
    (void)in_sizes; (void)n_in; (void)out_size;
    cudaFuncSetAttribute(gqa::attn_kernel, cudaFuncAttributeMaxDynamicSharedMemorySize, gqa::kSmemBytes);
    gqa::attn_kernel<<<gqa::kCtas, gqa::kThreads, gqa::kSmemBytes>>>(
        (const __nv_bfloat16*)d_in[0], (__nv_bfloat16*)d_out, gqa::make_map(d_in[1]), gqa::make_map(d_in[2]));
}
```

```cpp
#include <cuda.h>
#include <cuda_runtime.h>
#include <cuda_bf16.h>
#include <limits.h>
#include <stdint.h>

namespace gqa {

constexpr int kD = 128;
constexpr int kSk = 8192;
constexpr int kHeads = 64;
constexpr int kCtas = 2 * kHeads;
constexpr int kRows = 16;
constexpr int kTile = 128;
constexpr int kTiles = kSk / 2 / kTile;
constexpr int kUnits = 2 * kTiles;
constexpr int kUnitBytes = kTile * kD * 2;
constexpr int G = 4;
constexpr int kSupers = kTiles / G;

constexpr int kWarps = 8;
constexpr int kProducerWarp = kWarps;
constexpr int kMonitorWarp = kWarps + 1;
constexpr int kThreads = (kWarps + 2) * 32;

constexpr int kBoxKeys = 32;
constexpr int kBoxBytes = kBoxKeys * kD * 2;
constexpr int kBoxes = kTile / kBoxKeys;
constexpr int kGroupBytes = 8 * kD * 2;
constexpr int kGroupsPerBox = kBoxKeys / 8;
constexpr int kGroupsPerTile = kTile / 8;
constexpr int kStages = 6;

constexpr int kWindow0 = 6 * kCtas;
constexpr int kWindow1 = 3 * kCtas / 2;
constexpr int kTaperStart = 36;
constexpr uint32_t kProgressTotal = kCtas * (kUnits - 1);
constexpr int kPollBudget = 1024;
constexpr int kWaitLimit = 1 << 22;

constexpr int kSlotLast = (kUnits - 1) % kStages;
constexpr uint32_t kParityLast = ((kUnits - 1) / kStages) & 1;
static_assert(kSlotLast + 2 < kStages, "two spare ring slots are needed at the end");

constexpr int kFragBytes = 8 * 32 * 16;
constexpr int kQStride = kD * 2 + 16;
constexpr int kOffP = kStages * kUnitBytes;
constexpr int kOffPeerP = kOffP + G * kFragBytes;
constexpr int kOffQ = kOffPeerP + kFragBytes;
constexpr int kOffMax = kOffQ + kRows * kQStride;
constexpr int kOffSum = kOffMax + kRows * kWarps * 4;
constexpr int kOffPeerStat = kOffSum + kRows * kWarps * 4;
constexpr int kBarFull = kOffPeerStat + kRows * 8;
constexpr int kBarEmpty = kBarFull + 8 * kStages * kBoxes;
constexpr int kBarStat = kBarEmpty + 8 * kStages;
constexpr int kBarPartial = kBarStat + 8;
constexpr int kBarQ = kBarPartial + 8;
constexpr int kSmemBytes = kBarQ + 8 + 1024;

__device__ unsigned int g_progress;

__device__ __forceinline__ bool elect_one() {
    uint32_t p;
    asm volatile("{ .reg .pred P; elect.sync _|P, 0xffffffff; selp.u32 %0, 1, 0, P; }" : "=r"(p));
    return p != 0;
}
__device__ __forceinline__ void cluster_sync_relaxed() {
    asm volatile("barrier.cluster.arrive.relaxed.aligned;" ::: "memory");
    asm volatile("barrier.cluster.wait.acquire.aligned;" ::: "memory");
}
__device__ __forceinline__ void compute_sync() {
    asm volatile("bar.sync 1, %0;" ::"n"(kWarps * 32) : "memory");
}
__device__ __forceinline__ void mbar_init(uint32_t bar, uint32_t count) {
    asm volatile("mbarrier.init.shared::cta.b64 [%0], %1;" ::"r"(bar), "r"(count) : "memory");
}
__device__ __forceinline__ void mbar_init_fence() {
    asm volatile("fence.mbarrier_init.release.cluster;" ::: "memory");
}
__device__ __forceinline__ void mbar_expect_tx(uint32_t bar, uint32_t bytes) {
    asm volatile("mbarrier.arrive.expect_tx.shared::cta.b64 _, [%0], %1;" ::"r"(bar), "r"(bytes) : "memory");
}
__device__ __forceinline__ void mbar_arrive(uint32_t bar) {
    asm volatile("mbarrier.arrive.shared::cta.b64 _, [%0];" ::"r"(bar) : "memory");
}
__device__ __forceinline__ void mbar_wait(uint32_t bar, uint32_t parity) {
    asm volatile(
        "{\n"
        ".reg .pred P;\n"
        ".reg .u32 n;\n"
        "mov.u32 n, 0;\n"
        "WAIT_LOOP:\n"
        "mbarrier.try_wait.parity.shared::cta.b64 P, [%0], %1;\n"
        "@P bra WAIT_DONE;\n"
        "add.u32 n, n, 1;\n"
        "setp.lt.u32 P, n, %2;\n"
        "@P bra WAIT_LOOP;\n"
        "trap;\n"
        "WAIT_DONE:\n"
        "}\n" ::"r"(bar), "r"(parity), "n"(kWaitLimit) : "memory");
}
__device__ __forceinline__ bool mbar_test(uint32_t bar, uint32_t parity) {
    uint32_t ok;
    asm volatile("{ .reg .pred P; mbarrier.test_wait.parity.shared::cta.b64 P, [%1], %2; selp.u32 %0, 1, 0, P; }"
                 : "=r"(ok) : "r"(bar), "r"(parity) : "memory");
    return ok != 0;
}
__device__ __forceinline__ void mbar_wait_cluster(uint32_t bar, uint32_t parity) {
    asm volatile(
        "{\n"
        ".reg .pred P;\n"
        ".reg .u32 n;\n"
        "mov.u32 n, 0;\n"
        "WAIT_LOOP:\n"
        "mbarrier.try_wait.parity.relaxed.cluster.shared::cta.b64 P, [%0], %1;\n"
        "@P bra WAIT_DONE;\n"
        "add.u32 n, n, 1;\n"
        "setp.lt.u32 P, n, %2;\n"
        "@P bra WAIT_LOOP;\n"
        "trap;\n"
        "WAIT_DONE:\n"
        "fence.acquire.sync_restrict::shared::cluster.cluster;\n"
        "}\n" ::"r"(bar), "r"(parity), "n"(kWaitLimit) : "memory");
}
__device__ __forceinline__ bool mbar_test_cluster(uint32_t bar, uint32_t parity) {
    uint32_t ok;
    asm volatile("{ .reg .pred P; mbarrier.test_wait.parity.relaxed.cluster.shared::cta.b64 P, [%1], %2;"
                 " selp.u32 %0, 1, 0, P; fence.acquire.sync_restrict::shared::cluster.cluster; }"
                 : "=r"(ok) : "r"(bar), "r"(parity) : "memory");
    return ok != 0;
}
__device__ __forceinline__ uint64_t evict_first_policy() {
    uint64_t p;
    asm("createpolicy.fractional.L2::evict_first.b64 %0, 1.0;" : "=l"(p));
    return p;
}
__device__ __forceinline__ void tma_load_box(uint32_t dst, const CUtensorMap* map, int group, uint32_t bar) {
    asm volatile("cp.async.bulk.tensor.4d.shared::cluster.global.mbarrier::complete_tx::bytes.L2::cache_hint"
                 " [%0], [%1, {%3, %3, %3, %4}], [%2], %5;"
                 ::"r"(dst), "l"(map), "r"(bar), "r"(0), "r"(group), "l"(evict_first_policy()) : "memory");
}
__device__ __forceinline__ void tma_load_box_both(uint32_t dst, const CUtensorMap* map, int group, uint32_t bar) {
    asm volatile("cp.async.bulk.tensor.4d.shared::cluster.global.mbarrier::complete_tx::bytes.multicast::cluster.L2::cache_hint"
                 " [%0], [%1, {%3, %3, %3, %4}], [%2], %6, %5;"
                 ::"r"(dst), "l"(map), "r"(bar), "r"(0), "r"(group), "l"(evict_first_policy()), "h"((uint16_t)3) : "memory");
}
__device__ __forceinline__ void bulk_load(uint32_t dst, const void* src, uint32_t bytes, uint32_t bar) {
    asm volatile("cp.async.bulk.shared::cluster.global.mbarrier::complete_tx::bytes [%0], [%1], %2, [%3];"
                 ::"r"(dst), "l"(src), "r"(bytes), "r"(bar) : "memory");
}
__device__ __forceinline__ void prefetch_l2(const void* src, uint32_t bytes) {
    asm volatile("cp.async.bulk.prefetch.L2.global [%0], %1;" ::"l"(src), "r"(bytes) : "memory");
}
__device__ __forceinline__ void ldsm_x4(uint32_t (&r)[4], uint32_t addr) {
    asm volatile("ldmatrix.sync.aligned.m8n8.x4.shared.b16 {%0,%1,%2,%3}, [%4];"
                 : "=r"(r[0]), "=r"(r[1]), "=r"(r[2]), "=r"(r[3]) : "r"(addr) : "memory");
}
__device__ __forceinline__ void ldsm_x4_trans(uint32_t (&r)[4], uint32_t addr) {
    asm volatile("ldmatrix.sync.aligned.m8n8.x4.trans.shared.b16 {%0,%1,%2,%3}, [%4];"
                 : "=r"(r[0]), "=r"(r[1]), "=r"(r[2]), "=r"(r[3]) : "r"(addr) : "memory");
}
__device__ __forceinline__ void mma_bf16(float (&c)[4], const uint32_t (&a)[4], uint32_t b0, uint32_t b1) {
    asm volatile("mma.sync.aligned.m16n8k16.row.col.f32.bf16.bf16.f32 {%0,%1,%2,%3}, {%4,%5,%6,%7}, {%8,%9}, {%0,%1,%2,%3};"
                 : "+f"(c[0]), "+f"(c[1]), "+f"(c[2]), "+f"(c[3])
                 : "r"(a[0]), "r"(a[1]), "r"(a[2]), "r"(a[3]), "r"(b0), "r"(b1));
}
__device__ __forceinline__ float ex2(float x) {
    float y;
    asm("ex2.approx.ftz.f32 %0, %1;" : "=f"(y) : "f"(x));
    return y;
}
__device__ __forceinline__ uint32_t pack_bf16(float lo, float hi) {
    uint32_t r;
    asm("cvt.rn.bf16x2.f32 %0, %1, %2;" : "=r"(r) : "f"(hi), "f"(lo));
    return r;
}
__device__ __forceinline__ float2 lds64(uint32_t addr) {
    float2 v;
    asm volatile("ld.shared.v2.f32 {%0,%1}, [%2];" : "=f"(v.x), "=f"(v.y) : "r"(addr) : "memory");
    return v;
}
__device__ __forceinline__ float4 lds128(uint32_t addr) {
    float4 v;
    asm volatile("ld.shared.v4.f32 {%0,%1,%2,%3}, [%4];" : "=f"(v.x), "=f"(v.y), "=f"(v.z), "=f"(v.w) : "r"(addr) : "memory");
    return v;
}
__device__ __forceinline__ void load_frags(uint32_t (&r)[8][4], uint32_t addr) {
#pragma unroll
    for (int ks = 0; ks < 8; ++ks)
        asm volatile("ld.shared.v4.u32 {%0,%1,%2,%3}, [%4];"
                     : "=r"(r[ks][0]), "=r"(r[ks][1]), "=r"(r[ks][2]), "=r"(r[ks][3]) : "r"(addr + ks * 512) : "memory");
}
__device__ __forceinline__ void sts32(uint32_t addr, float v) {
    asm volatile("st.shared.f32 [%0], %1;" ::"r"(addr), "f"(v) : "memory");
}
__device__ __forceinline__ void sts128(uint32_t addr, uint32_t a, uint32_t b, uint32_t c, uint32_t d) {
    asm volatile("st.shared.v4.u32 [%0], {%1,%2,%3,%4};" ::"r"(addr), "r"(a), "r"(b), "r"(c), "r"(d) : "memory");
}
__device__ __forceinline__ void stg32(uint64_t addr, uint32_t v) {
    asm volatile("st.global.u32 [%0], %1;" ::"l"(addr), "r"(v) : "memory");
}
__device__ __forceinline__ uint32_t map_to_cta(uint32_t addr, uint32_t rank) {
    uint32_t r;
    asm("mapa.shared::cluster.u32 %0, %1, %2;" : "=r"(r) : "r"(addr), "r"(rank));
    return r;
}
__device__ __forceinline__ void st_async_v2(uint32_t addr, float a, float b, uint32_t bar) {
    asm volatile("st.async.weak.shared::cluster.mbarrier::complete_tx::bytes.v2.f32 [%0], {%1,%2}, [%3];"
                 ::"r"(addr), "f"(a), "f"(b), "r"(bar) : "memory");
}
__device__ __forceinline__ void st_async_v4(uint32_t addr, uint32_t a, uint32_t b, uint32_t c, uint32_t d, uint32_t bar) {
    asm volatile("st.async.weak.shared::cluster.mbarrier::complete_tx::bytes.v4.b32 [%0], {%1,%2,%3,%4}, [%5];"
                 ::"r"(addr), "r"(a), "r"(b), "r"(c), "r"(d), "r"(bar) : "memory");
}
__device__ __forceinline__ void progress_tick() {
    asm volatile("red.relaxed.gpu.global.inc.u32 [%0], %1;" ::"l"(&g_progress), "r"(kProgressTotal - 1) : "memory");
}
__device__ __forceinline__ int read_progress() {
    int v;
    asm volatile("ld.relaxed.gpu.global.u32 %0, [%1];" : "=r"(v) : "l"(&g_progress) : "memory");
    return v;
}
__device__ __forceinline__ float row_max(uint32_t addr) {
    const float4 a = lds128(addr), b = lds128(addr + 16);
    return fmaxf(fmaxf(fmaxf(a.x, a.y), fmaxf(a.z, a.w)), fmaxf(fmaxf(b.x, b.y), fmaxf(b.z, b.w)));
}
__device__ __forceinline__ float row_sum(uint32_t addr) {
    const float4 a = lds128(addr), b = lds128(addr + 16);
    return ((a.x + a.y) + (a.z + a.w)) + ((b.x + b.y) + (b.z + b.w));
}

__device__ __forceinline__ void issue_unit(uint32_t smem, int stage, int u, int group0,
                                           const CUtensorMap* kmap, const CUtensorMap* vmap) {
    const CUtensorMap* map = (u % (2 * G)) < G ? kmap : vmap;
    const int group = group0 + ((u / (2 * G)) * G + u % G) * kGroupsPerTile;
    const uint32_t bar = smem + kBarFull + 8 * kBoxes * stage;
    const uint32_t dst = smem + stage * kUnitBytes;
#pragma unroll
    for (int b = 0; b < kBoxes; ++b) {
        mbar_expect_tx(bar + 8 * b, kBoxBytes);
        tma_load_box(dst + b * kBoxBytes, map, group + b * kGroupsPerBox, bar + 8 * b);
    }
}

__global__ void __cluster_dims__(2, 1, 1) __launch_bounds__(kThreads, 1)
attn_kernel(const __nv_bfloat16* __restrict__ q, const __nv_bfloat16* __restrict__ k,
            const __nv_bfloat16* __restrict__ v, __nv_bfloat16* __restrict__ out,
            const __grid_constant__ CUtensorMap kmap, const __grid_constant__ CUtensorMap vmap) {
    extern __shared__ __align__(128) unsigned char smem_raw[];
    const uint32_t smem = ((uint32_t)__cvta_generic_to_shared(smem_raw) + 1023u) & ~1023u;
    const int warp = threadIdx.x >> 5;
    const int lane = threadIdx.x & 31;
    const int cta = blockIdx.x;
    const int head = cta >> 1;
    const uint32_t rank = cta & 1;
    const int group0 = cta * (kTiles * kGroupsPerTile);

    if (warp == 0 && elect_one()) prefetch_l2(k + (size_t)group0 * 8 * kD, kUnitBytes);
    if (warp == 2 && elect_one()) prefetch_l2(v + (size_t)group0 * 8 * kD, kD * 2);
    if (warp == 1 && elect_one()) {
#pragma unroll
        for (int b = 0; b < kBoxes; ++b) mbar_init(smem + kBarFull + 8 * b, 1);
        mbar_init_fence();
        issue_unit(smem, 0, 0, group0, &kmap, &vmap);
    }

    if (warp == kProducerWarp) {
        const bool leader = elect_one();
        int seen = 0;
        if (leader) {
            seen = read_progress();
            mbar_init(smem + kBarQ, 1);
            mbar_init_fence();
            mbar_expect_tx(smem + kBarQ, kRows * kD * 2);
#pragma unroll 4
            for (int r = 0; r < kRows; ++r)
                bulk_load(smem + kOffQ + r * kQStride, q + ((size_t)head * kRows + r) * kD, kD * 2, smem + kBarQ);
#pragma unroll 1
            for (int u = 1; u < kStages; ++u) {
#pragma unroll
                for (int b = 0; b < kBoxes; ++b) mbar_init(smem + kBarFull + 8 * (kBoxes * u + b), 1);
                mbar_init_fence();
                issue_unit(smem, u, u, group0, &kmap, &vmap);
            }
        }
        __syncwarp();
        cluster_sync_relaxed();
        if (leader) {
            int stage = 0;
            uint32_t parity = 0;
            int budget = kPollBudget;
#pragma unroll 1
            for (int u = kStages; u < kUnits; ++u) {
                mbar_wait(smem + kBarEmpty + 8 * stage, parity);
                if (u == kUnits - 1) {
                    mbar_wait(smem + kBarEmpty + 8 * (kSlotLast + 1), parity);
                    mbar_wait_cluster(smem + kBarStat, 0);
                }
                const int window = u <= kTaperStart
                    ? kWindow0 : kWindow0 - (kWindow0 - kWindow1) * (u - kTaperStart) / (kUnits - 1 - kTaperStart);
                const int need = u * kCtas - window;
                while (seen < need && budget > 0) {
                    const int now = read_progress();
                    seen = now < seen ? INT_MAX : now;
                    --budget;
                }
                if (u < kUnits - 1) issue_unit(smem, stage, u, group0, &kmap, &vmap);
                if (++stage == kStages) { stage = 0; parity ^= 1; }
            }
#pragma unroll
            for (int b = 0; b < 2 * kBoxes; ++b) mbar_expect_tx(smem + kBarFull + 8 * (kBoxes * kSlotLast + b), kBoxBytes);
#pragma unroll
            for (int b = 0; b < kBoxes; ++b)
                tma_load_box_both(smem + (kSlotLast + rank) * kUnitBytes + b * kBoxBytes, &vmap,
                                  group0 + (kTiles - 1) * kGroupsPerTile + b * kGroupsPerBox,
                                  smem + kBarFull + 8 * (kBoxes * (kSlotLast + rank) + b));
        }
        return;
    }

    if (warp == kMonitorWarp) {
        cluster_sync_relaxed();
        if (lane == 0) {
            int stage = 0;
            uint32_t parity = 0;
#pragma unroll 1
            for (int u = 0; u < kUnits - 1; ++u) {
#pragma unroll
                for (int b = 0; b < kBoxes; ++b) mbar_wait(smem + kBarFull + 8 * (kBoxes * stage + b), parity);
                progress_tick();
                mbar_arrive(smem + kBarEmpty + 8 * stage);
                if (++stage == kStages) { stage = 0; parity ^= 1; }
            }
        }
        return;
    }

    if (threadIdx.x == 3 * 32) {
        for (int s = 0; s < kStages; ++s) mbar_init(smem + kBarEmpty + 8 * s, kWarps + 1);
        mbar_init(smem + kBarStat, 1);
        mbar_init(smem + kBarPartial, 1 + kWarps / 2);
        mbar_init_fence();
        mbar_expect_tx(smem + kBarStat, kRows * 8 + kFragBytes);
        mbar_expect_tx(smem + kBarPartial, kRows * (kD / 2) * 4);
    }
    __syncwarp();
    cluster_sync_relaxed();

    const float c = 0.08838834764831845f * 1.4426950408889634f;
    const int g = lane >> 2;
    const int t4 = lane & 3;
    const int mi = lane >> 3;
    const int r8 = lane & 7;
    const uint32_t q_addr = smem + kOffQ + ((mi & 1) * 8 + r8) * kQStride + (mi >> 1) * 16;
    const uint32_t k_off = warp * 2 * kGroupBytes + r8 * 128 + ((mi ^ r8) << 4);
    const uint32_t k_bar = smem + kBarFull + 8 * (warp * 16 / kBoxKeys);
    const int vc = warp * 2 + (mi >> 1);
    const uint32_t v_off = (mi & 1) * kGroupBytes + (vc >> 3) * 1024 + r8 * 128 + (((vc & 7) ^ r8) << 4);
    const uint32_t stat_w = smem + kOffMax + (g * kWarps + warp) * 4;
    const uint32_t stat_r = smem + kOffMax + g * kWarps * 4;
    constexpr int kRow8 = 8 * kWarps * 4, kSum = kOffSum - kOffMax;
    const uint32_t p_w = smem + kOffP + threadIdx.x * 16;
    const uint32_t p_r = smem + kOffP + lane * 16;
    const uint32_t peer = map_to_cta(smem, rank ^ 1);
    uint64_t out_addr = __cvta_generic_to_global(out + ((size_t)head * kRows + g) * kD + rank * 64 + warp * 8 + t4 * 2);
    asm volatile("" : "+l"(out_addr));

    float m0 = -INFINITY, m1 = -INFINITY, l0 = 0.f, l1 = 0.f;
    float f0 = 0.f, f1 = 0.f, pf0 = 0.f, pf1 = 0.f;
    float o[2][2][4] = {};
    uint32_t pa[G - 1][8][4];

    mbar_wait(smem + kBarQ, 0);
    int stage = 0;
    uint32_t parity = 0;
#pragma unroll 1
    for (int st = 0; st < kSupers; ++st) {
        const bool last = st == kSupers - 1;

        uint32_t qa[8][4];
#pragma unroll
        for (int ks = 0; ks < 8; ++ks) ldsm_x4(qa[ks], q_addr + ks * 32);
        float s[G][2][4] = {};
#pragma unroll
        for (int i = 0; i < G; ++i) {
            mbar_wait(k_bar + 8 * kBoxes * stage, parity);
            const uint32_t base = smem + stage * kUnitBytes;
#pragma unroll
            for (int j = 0; j < 4; ++j) {
                uint32_t b[2][4];
#pragma unroll
                for (int n = 0; n < 2; ++n)
                    ldsm_x4(b[n], base + (k_off ^ ((j & 1) * 64)) + n * kGroupBytes + (j >> 1) * 1024);
#pragma unroll
                for (int n = 0; n < 2; ++n) mma_bf16(s[i][n], qa[2 * j], b[n][0], b[n][1]);
#pragma unroll
                for (int n = 0; n < 2; ++n) mma_bf16(s[i][n], qa[2 * j + 1], b[n][2], b[n][3]);
            }
            if (lane == 0) mbar_arrive(smem + kBarEmpty + 8 * stage);
            if (++stage == kStages) { stage = 0; parity ^= 1; }
        }

        float mx0 = m0, mx1 = m1;
#pragma unroll
        for (int i = 0; i < G; ++i)
#pragma unroll
            for (int n = 0; n < 2; ++n) {
                mx0 = fmaxf(mx0, fmaxf(s[i][n][0], s[i][n][1]));
                mx1 = fmaxf(mx1, fmaxf(s[i][n][2], s[i][n][3]));
            }
        mx0 = fmaxf(mx0, __shfl_xor_sync(0xffffffffu, mx0, 1));
        mx1 = fmaxf(mx1, __shfl_xor_sync(0xffffffffu, mx1, 1));
        mx0 = fmaxf(mx0, __shfl_xor_sync(0xffffffffu, mx0, 2));
        mx1 = fmaxf(mx1, __shfl_xor_sync(0xffffffffu, mx1, 2));
        if (t4 == 0) {
            sts32(stat_w, mx0);
            sts32(stat_w + kRow8, mx1);
        }
        compute_sync();
        const float mn0 = row_max(stat_r), mn1 = row_max(stat_r + kRow8);
        const float a0 = ex2((m0 - mn0) * c), a1 = ex2((m1 - mn1) * c);
        m0 = mn0;
        m1 = mn1;
        const float b0 = -mn0 * c, b1 = -mn1 * c;
        l0 *= a0;
        l1 *= a1;
#pragma unroll
        for (int i = 0; i < G; ++i) {
#pragma unroll
            for (int n = 0; n < 2; ++n) {
                s[i][n][0] = ex2(fmaf(s[i][n][0], c, b0));
                s[i][n][1] = ex2(fmaf(s[i][n][1], c, b0));
                s[i][n][2] = ex2(fmaf(s[i][n][2], c, b1));
                s[i][n][3] = ex2(fmaf(s[i][n][3], c, b1));
                l0 += s[i][n][0] + s[i][n][1];
                l1 += s[i][n][2] + s[i][n][3];
            }
            const uint32_t p0 = pack_bf16(s[i][0][0], s[i][0][1]), p1 = pack_bf16(s[i][0][2], s[i][0][3]);
            const uint32_t p2 = pack_bf16(s[i][1][0], s[i][1][1]), p3 = pack_bf16(s[i][1][2], s[i][1][3]);
            sts128(p_w + i * kFragBytes, p0, p1, p2, p3);
            if (i == G - 1 && last) st_async_v4(peer + kOffPeerP + threadIdx.x * 16, p0, p1, p2, p3, peer + kBarStat);
        }
        if (last) {
            l0 += __shfl_xor_sync(0xffffffffu, l0, 1);
            l1 += __shfl_xor_sync(0xffffffffu, l1, 1);
            l0 += __shfl_xor_sync(0xffffffffu, l0, 2);
            l1 += __shfl_xor_sync(0xffffffffu, l1, 2);
            if (t4 == 0) {
                sts32(stat_w + kSum, l0);
                sts32(stat_w + kSum + kRow8, l1);
            }
        }
#pragma unroll
        for (int h = 0; h < 2; ++h)
#pragma unroll
            for (int n = 0; n < 2; ++n) {
                o[h][n][0] *= a0; o[h][n][1] *= a0; o[h][n][2] *= a1; o[h][n][3] *= a1;
            }
        compute_sync();
        load_frags(pa[0], p_r);

        if (last) {
            l0 = row_sum(stat_r + kSum);
            l1 = row_sum(stat_r + kSum + kRow8);
            if (warp == 0 && t4 == 0) {
                st_async_v2(peer + kOffPeerStat + g * 8, m0, l0, peer + kBarStat);
                st_async_v2(peer + kOffPeerStat + g * 8 + 64, m1, l1, peer + kBarStat);
            }
            mbar_wait_cluster(smem + kBarStat, 0);
            const float2 x0 = lds64(smem + kOffPeerStat + g * 8), x1 = lds64(smem + kOffPeerStat + g * 8 + 64);
            const float mf0 = fmaxf(m0, x0.x), mf1 = fmaxf(m1, x1.x);
            const float e0 = ex2((m0 - mf0) * c), e1 = ex2((m1 - mf1) * c);
            const float pe0 = ex2((x0.x - mf0) * c), pe1 = ex2((x1.x - mf1) * c);
            const float r0 = 1.f / (l0 * e0 + x0.y * pe0), r1 = 1.f / (l1 * e1 + x1.y * pe1);
            f0 = e0 * r0;
            f1 = e1 * r1;
            pf0 = pe0 * r0;
            pf1 = pe1 * r1;
        }

        uint32_t vb[2][2][4];
        int prev_stage = stage;
        bool landed = false;
        auto pv_mma = [&](int y) {
#pragma unroll
            for (int h = 0; h < 2; ++h) {
                const uint32_t(&a)[4] = pa[(y / kBoxes) % (G - 1)][2 * (y % kBoxes) + h];
                mma_bf16(o[h][0], a, vb[y & 1][h][0], vb[y & 1][h][1]);
                mma_bf16(o[h][1], a, vb[y & 1][h][2], vb[y & 1][h][3]);
            }
        };
#pragma unroll
        for (int x = 0; x <= G * kBoxes; ++x) {
            const int bx = x % kBoxes;
            if (x == kBoxes) {
#pragma unroll
                for (int i = 1; i < G - 1; ++i) load_frags(pa[i], p_r + i * kFragBytes);
            }
            if (x == (G - 1) * kBoxes && last) {
                pv_mma(x - 1);
                break;
            }
            if (x < G * kBoxes) {
                if (!landed) mbar_wait(smem + kBarFull + 8 * (kBoxes * stage + bx), parity);
                __syncwarp();
                const uint32_t base = smem + stage * kUnitBytes + bx * kBoxBytes + v_off;
                if (bx == kBoxes - 1) {
                    prev_stage = stage;
                    if (++stage == kStages) { stage = 0; parity ^= 1; }
                }
                if (x + 1 < G * kBoxes) landed = mbar_test(smem + kBarFull + 8 * (kBoxes * stage + (bx + 1) % kBoxes), parity);
#pragma unroll
                for (int h = 0; h < 2; ++h) ldsm_x4_trans(vb[x & 1][h], base + h * 2 * kGroupBytes);
            }
            if (x > 0) {
                pv_mma(x - 1);
                if (bx == 0) {
                    if (lane == 0) mbar_arrive(smem + kBarEmpty + 8 * prev_stage);
                    if (x == kBoxes) load_frags(pa[0], p_r + (G - 1) * kFragBytes);
                    if (x == 2 * kBoxes && last) load_frags(pa[1], p_r + (kOffPeerP - kOffP));
                }
            }
        }
    }

    constexpr int kOffPartial = (kSlotLast + 2) * kUnitBytes, kHalf = kRows * (kD / 2) * 4;
    const bool mine = (warp >> 2) == rank;
#pragma unroll
    for (int n = 0; n < 2; ++n) {
        const uint32_t off = kOffPartial + ((2 * warp + n) & 7) * 512 + lane * 16;
        const uint32_t v0 = __float_as_uint((o[0][n][0] + o[1][n][0]) * f0), v1 = __float_as_uint((o[0][n][1] + o[1][n][1]) * f0);
        const uint32_t v2 = __float_as_uint((o[0][n][2] + o[1][n][2]) * f1), v3 = __float_as_uint((o[0][n][3] + o[1][n][3]) * f1);
        if (mine) sts128(smem + off, v0, v1, v2, v3);
        else st_async_v4(peer + off + kHalf, v0, v1, v2, v3, peer + kBarPartial);
    }
    __syncwarp();
    if (mine && lane == 0) mbar_arrive(smem + kBarPartial);

    const uint32_t w_off = mi * kGroupBytes + rank * 1024 + r8 * 128 + ((warp ^ r8) << 4);
    const uint32_t slot[2] = {kSlotLast + rank, kSlotLast + 1 - rank};
    const uint32_t part = smem + kOffPartial + threadIdx.x * 16;
    float acc[2][2][4] = {};
    uint32_t wb[2][4] = {};
    bool landed = false, early = false;
    float4 x0, x1;
    auto last_mma = [&](int y) {
        mma_bf16(acc[y & 1][0], pa[y & 1][2 * (y >> 1)], wb[y & 1][0], wb[y & 1][1]);
        mma_bf16(acc[y & 1][1], pa[y & 1][2 * (y >> 1) + 1], wb[y & 1][2], wb[y & 1][3]);
    };
#pragma unroll
    for (int x = 0; x <= 2 * kBoxes; ++x) {
        const bool final_box = x == 2 * kBoxes - 1;
        if (final_box) {
            last_mma(x - 1);
            early = mbar_test_cluster(smem + kBarPartial, 0);
            if (early) {
                x0 = lds128(part);
                x1 = lds128(part + kHalf);
            }
        }
        if (x < 2 * kBoxes) {
            if (!landed) mbar_wait(smem + kBarFull + 8 * (kBoxes * slot[x & 1] + (x >> 1)), kParityLast);
            __syncwarp();
            if (!final_box) landed = mbar_test(smem + kBarFull + 8 * (kBoxes * slot[(x + 1) & 1] + ((x + 1) >> 1)), kParityLast);
            ldsm_x4_trans(wb[x & 1], smem + slot[x & 1] * kUnitBytes + (x >> 1) * kBoxBytes + w_off);
        }
        if (x > 0 && !final_box) last_mma(x - 1);
    }
    if (!early) {
        mbar_wait_cluster(smem + kBarPartial, 0);
        x0 = lds128(part);
        x1 = lds128(part + kHalf);
    }
    const float r0 = fmaf(acc[1][0][0] + acc[1][1][0], pf0, fmaf(acc[0][0][0] + acc[0][1][0], f0, x0.x + x1.x));
    const float r1 = fmaf(acc[1][0][1] + acc[1][1][1], pf0, fmaf(acc[0][0][1] + acc[0][1][1], f0, x0.y + x1.y));
    const float r2 = fmaf(acc[1][0][2] + acc[1][1][2], pf1, fmaf(acc[0][0][2] + acc[0][1][2], f1, x0.z + x1.z));
    const float r3 = fmaf(acc[1][0][3] + acc[1][1][3], pf1, fmaf(acc[0][0][3] + acc[0][1][3], f1, x0.w + x1.w));
    stg32(out_addr, pack_bf16(r0, r1));
    stg32(out_addr + 8 * kD * 2, pack_bf16(r2, r3));
}

typedef CUresult (*EncodeTiledFn)(CUtensorMap*, CUtensorMapDataType, cuuint32_t, void*, const cuuint64_t*,
                                  const cuuint64_t*, const cuuint32_t*, const cuuint32_t*, CUtensorMapInterleave,
                                  CUtensorMapSwizzle, CUtensorMapL2promotion, CUtensorMapFloatOOBfill);

inline CUtensorMap make_map(const void* ptr) {
    static EncodeTiledFn encode = nullptr;
    if (!encode) {
        cudaDriverEntryPointQueryResult status;
        cudaGetDriverEntryPoint("cuTensorMapEncodeTiled", (void**)&encode, cudaEnableDefault, &status);
    }
    CUtensorMap map;
    const cuuint64_t dims[4] = {64, 8, 2, (cuuint64_t)kHeads * kSk / 8};
    const cuuint64_t strides[3] = {kD * 2, 128, kGroupBytes};
    const cuuint32_t box[4] = {64, 8, 2, kGroupsPerBox};
    const cuuint32_t elem_strides[4] = {1, 1, 1, 1};
    encode(&map, CU_TENSOR_MAP_DATA_TYPE_BFLOAT16, 4, const_cast<void*>(ptr), dims, strides, box, elem_strides,
           CU_TENSOR_MAP_INTERLEAVE_NONE, CU_TENSOR_MAP_SWIZZLE_128B, CU_TENSOR_MAP_L2_PROMOTION_L2_256B,
           CU_TENSOR_MAP_FLOAT_OOB_FILL_NONE);
    return map;
}

}

extern "C" void kernel_launch(void* const* d_in, const int* in_sizes, int n_in, void* d_out, int out_size) {
    (void)in_sizes; (void)n_in; (void)out_size;
    cudaFuncSetAttribute(gqa::attn_kernel, cudaFuncAttributeMaxDynamicSharedMemorySize, gqa::kSmemBytes);
    gqa::attn_kernel<<<gqa::kCtas, gqa::kThreads, gqa::kSmemBytes>>>(
        (const __nv_bfloat16*)d_in[0], (const __nv_bfloat16*)d_in[1], (const __nv_bfloat16*)d_in[2],
        (__nv_bfloat16*)d_out, gqa::make_map(d_in[1]), gqa::make_map(d_in[2]));
}
```

```cpp
#include <cuda.h>
#include <cuda_runtime.h>
#include <cuda_bf16.h>
#include <limits.h>
#include <stdint.h>

namespace gqa {

constexpr int kD = 128;
constexpr int kSk = 8192;
constexpr int kHeads = 64;
constexpr int kCtas = 2 * kHeads;
constexpr int kRows = 16;
constexpr int kTile = 128;
constexpr int kTiles = kSk / 2 / kTile;
constexpr int kUnits = 2 * kTiles;
constexpr int kUnitBytes = kTile * kD * 2;
constexpr int G = 4;
constexpr int kSupers = kTiles / G;

constexpr int kWarps = 8;
constexpr int kProducerWarp = kWarps;
constexpr int kMonitorWarp = kWarps + 1;
constexpr int kThreads = (kWarps + 2) * 32;

constexpr int kBoxKeys = 32;
constexpr int kBoxBytes = kBoxKeys * kD * 2;
constexpr int kBoxes = kTile / kBoxKeys;
constexpr int kGroupBytes = 8 * kD * 2;
constexpr int kGroupsPerBox = kBoxKeys / 8;
constexpr int kGroupsPerTile = kTile / 8;
constexpr int kStages = 6;

constexpr int kWindow0 = 6 * kCtas;
constexpr int kWindow1 = 13 * kCtas / 8;
constexpr int kTaperStart = 30;
constexpr int kLastRankDelay = 88;
constexpr int kLastHalfDelay = 36;
constexpr uint32_t kProgressTotal = kCtas * (kUnits - 1);
constexpr int kPollBudget = 1024;
constexpr int kWaitLimit = 1 << 22;

constexpr int kSlotLast = (kUnits - 1) % kStages;
constexpr uint32_t kParityLast = ((kUnits - 1) / kStages) & 1;
static_assert(kSlotLast + 2 < kStages, "two spare ring slots are needed at the end");
static_assert(kUnits - 1 - kStages >= kUnits - 2 * G && kUnits + 1 - kStages < kUnits - G,
              "these three slots must last have held K tiles of the final softmax update");

constexpr int kFragBytes = 8 * 32 * 16;
constexpr int kQStride = kD * 2 + 16;
constexpr int kOffP = kStages * kUnitBytes;
constexpr int kOffPeerP = kOffP + G * kFragBytes;
constexpr int kOffQ = kOffPeerP + kFragBytes;
constexpr int kOffMax = kOffQ + kRows * kQStride;
constexpr int kOffSum = kOffMax + kRows * kWarps * 4;
constexpr int kOffPeerStat = kOffSum + kRows * kWarps * 4;
constexpr int kBarFull = kOffPeerStat + kRows * 8;
constexpr int kBarEmpty = kBarFull + 8 * kStages * kBoxes;
constexpr int kBarStat = kBarEmpty + 8 * kStages;
constexpr int kBarPartial = kBarStat + 8;
constexpr int kBarQ = kBarPartial + 8;
constexpr int kSmemBytes = kBarQ + 8 + 1024;

__device__ unsigned int g_progress;

__device__ __forceinline__ bool elect_one() {
    uint32_t p;
    asm volatile("{ .reg .pred P; elect.sync _|P, 0xffffffff; selp.u32 %0, 1, 0, P; }" : "=r"(p));
    return p != 0;
}
__device__ __forceinline__ void cluster_sync_relaxed() {
    asm volatile("barrier.cluster.arrive.relaxed.aligned;" ::: "memory");
    asm volatile("barrier.cluster.wait.acquire.aligned;" ::: "memory");
}
__device__ __forceinline__ void compute_sync() {
    asm volatile("bar.sync 1, %0;" ::"n"(kWarps * 32) : "memory");
}
__device__ __forceinline__ void mbar_init(uint32_t bar, uint32_t count) {
    asm volatile("mbarrier.init.shared::cta.b64 [%0], %1;" ::"r"(bar), "r"(count) : "memory");
}
__device__ __forceinline__ void mbar_init_fence() {
    asm volatile("fence.mbarrier_init.release.cluster;" ::: "memory");
}
__device__ __forceinline__ void mbar_expect_tx(uint32_t bar, uint32_t bytes) {
    asm volatile("mbarrier.arrive.expect_tx.shared::cta.b64 _, [%0], %1;" ::"r"(bar), "r"(bytes) : "memory");
}
__device__ __forceinline__ void mbar_arrive(uint32_t bar) {
    asm volatile("mbarrier.arrive.shared::cta.b64 _, [%0];" ::"r"(bar) : "memory");
}
__device__ __forceinline__ void mbar_wait(uint32_t bar, uint32_t parity) {
    asm volatile(
        "{\n"
        ".reg .pred P;\n"
        ".reg .u32 n;\n"
        "mov.u32 n, 0;\n"
        "WAIT_LOOP:\n"
        "mbarrier.try_wait.parity.shared::cta.b64 P, [%0], %1;\n"
        "@P bra WAIT_DONE;\n"
        "add.u32 n, n, 1;\n"
        "setp.lt.u32 P, n, %2;\n"
        "@P bra WAIT_LOOP;\n"
        "trap;\n"
        "WAIT_DONE:\n"
        "}\n" ::"r"(bar), "r"(parity), "n"(kWaitLimit) : "memory");
}
__device__ __forceinline__ bool mbar_test(uint32_t bar, uint32_t parity) {
    uint32_t ok;
    asm volatile("{ .reg .pred P; mbarrier.test_wait.parity.shared::cta.b64 P, [%1], %2; selp.u32 %0, 1, 0, P; }"
                 : "=r"(ok) : "r"(bar), "r"(parity) : "memory");
    return ok != 0;
}
__device__ __forceinline__ void mbar_wait_cluster(uint32_t bar, uint32_t parity) {
    asm volatile(
        "{\n"
        ".reg .pred P;\n"
        ".reg .u32 n;\n"
        "mov.u32 n, 0;\n"
        "WAIT_LOOP:\n"
        "mbarrier.try_wait.parity.relaxed.cluster.shared::cta.b64 P, [%0], %1;\n"
        "@P bra WAIT_DONE;\n"
        "add.u32 n, n, 1;\n"
        "setp.lt.u32 P, n, %2;\n"
        "@P bra WAIT_LOOP;\n"
        "trap;\n"
        "WAIT_DONE:\n"
        "fence.acquire.sync_restrict::shared::cluster.cluster;\n"
        "}\n" ::"r"(bar), "r"(parity), "n"(kWaitLimit) : "memory");
}
__device__ __forceinline__ bool mbar_test_cluster(uint32_t bar, uint32_t parity) {
    uint32_t ok;
    asm volatile("{ .reg .pred P; mbarrier.test_wait.parity.relaxed.cluster.shared::cta.b64 P, [%1], %2;"
                 " selp.u32 %0, 1, 0, P; fence.acquire.sync_restrict::shared::cluster.cluster; }"
                 : "=r"(ok) : "r"(bar), "r"(parity) : "memory");
    return ok != 0;
}
__device__ __forceinline__ uint64_t evict_first_policy() {
    uint64_t p;
    asm("createpolicy.fractional.L2::evict_first.b64 %0, 1.0;" : "=l"(p));
    return p;
}
__device__ __forceinline__ void tma_load_box(uint32_t dst, const CUtensorMap* map, int group, uint32_t bar) {
    asm volatile("cp.async.bulk.tensor.4d.shared::cluster.global.mbarrier::complete_tx::bytes.L2::cache_hint"
                 " [%0], [%1, {%3, %3, %3, %4}], [%2], %5;"
                 ::"r"(dst), "l"(map), "r"(bar), "r"(0), "r"(group), "l"(evict_first_policy()) : "memory");
}
__device__ __forceinline__ void tma_load_box_both(uint32_t dst, const CUtensorMap* map, int group, uint32_t bar) {
    asm volatile("cp.async.bulk.tensor.4d.shared::cluster.global.mbarrier::complete_tx::bytes.multicast::cluster.L2::cache_hint"
                 " [%0], [%1, {%3, %3, %3, %4}], [%2], %6, %5;"
                 ::"r"(dst), "l"(map), "r"(bar), "r"(0), "r"(group), "l"(evict_first_policy()), "h"((uint16_t)3) : "memory");
}
__device__ __forceinline__ void bulk_load(uint32_t dst, const void* src, uint32_t bytes, uint32_t bar) {
    asm volatile("cp.async.bulk.shared::cluster.global.mbarrier::complete_tx::bytes [%0], [%1], %2, [%3];"
                 ::"r"(dst), "l"(src), "r"(bytes), "r"(bar) : "memory");
}
__device__ __forceinline__ void prefetch_l2(const void* src, uint32_t bytes) {
    asm volatile("cp.async.bulk.prefetch.L2.global [%0], %1;" ::"l"(src), "r"(bytes) : "memory");
}
__device__ __forceinline__ void ldsm_x4(uint32_t (&r)[4], uint32_t addr) {
    asm volatile("ldmatrix.sync.aligned.m8n8.x4.shared.b16 {%0,%1,%2,%3}, [%4];"
                 : "=r"(r[0]), "=r"(r[1]), "=r"(r[2]), "=r"(r[3]) : "r"(addr) : "memory");
}
__device__ __forceinline__ void ldsm_x4_trans(uint32_t (&r)[4], uint32_t addr) {
    asm volatile("ldmatrix.sync.aligned.m8n8.x4.trans.shared.b16 {%0,%1,%2,%3}, [%4];"
                 : "=r"(r[0]), "=r"(r[1]), "=r"(r[2]), "=r"(r[3]) : "r"(addr) : "memory");
}
__device__ __forceinline__ void mma_bf16(float (&c)[4], const uint32_t (&a)[4], uint32_t b0, uint32_t b1) {
    asm volatile("mma.sync.aligned.m16n8k16.row.col.f32.bf16.bf16.f32 {%0,%1,%2,%3}, {%4,%5,%6,%7}, {%8,%9}, {%0,%1,%2,%3};"
                 : "+f"(c[0]), "+f"(c[1]), "+f"(c[2]), "+f"(c[3])
                 : "r"(a[0]), "r"(a[1]), "r"(a[2]), "r"(a[3]), "r"(b0), "r"(b1));
}
__device__ __forceinline__ float ex2(float x) {
    float y;
    asm("ex2.approx.ftz.f32 %0, %1;" : "=f"(y) : "f"(x));
    return y;
}
__device__ __forceinline__ uint32_t pack_bf16(float lo, float hi) {
    uint32_t r;
    asm("cvt.rn.bf16x2.f32 %0, %1, %2;" : "=r"(r) : "f"(hi), "f"(lo));
    return r;
}
__device__ __forceinline__ float2 lds64(uint32_t addr) {
    float2 v;
    asm volatile("ld.shared.v2.f32 {%0,%1}, [%2];" : "=f"(v.x), "=f"(v.y) : "r"(addr) : "memory");
    return v;
}
__device__ __forceinline__ float4 lds128(uint32_t addr) {
    float4 v;
    asm volatile("ld.shared.v4.f32 {%0,%1,%2,%3}, [%4];" : "=f"(v.x), "=f"(v.y), "=f"(v.z), "=f"(v.w) : "r"(addr) : "memory");
    return v;
}
__device__ __forceinline__ void load_frags(uint32_t (&r)[8][4], uint32_t addr) {
#pragma unroll
    for (int ks = 0; ks < 8; ++ks)
        asm volatile("ld.shared.v4.u32 {%0,%1,%2,%3}, [%4];"
                     : "=r"(r[ks][0]), "=r"(r[ks][1]), "=r"(r[ks][2]), "=r"(r[ks][3]) : "r"(addr + ks * 512) : "memory");
}
__device__ __forceinline__ void sts32(uint32_t addr, float v) {
    asm volatile("st.shared.f32 [%0], %1;" ::"r"(addr), "f"(v) : "memory");
}
__device__ __forceinline__ void sts128(uint32_t addr, uint32_t a, uint32_t b, uint32_t c, uint32_t d) {
    asm volatile("st.shared.v4.u32 [%0], {%1,%2,%3,%4};" ::"r"(addr), "r"(a), "r"(b), "r"(c), "r"(d) : "memory");
}
__device__ __forceinline__ void stg32(uint64_t addr, uint32_t v) {
    asm volatile("st.global.u32 [%0], %1;" ::"l"(addr), "r"(v) : "memory");
}
__device__ __forceinline__ uint32_t map_to_cta(uint32_t addr, uint32_t rank) {
    uint32_t r;
    asm("mapa.shared::cluster.u32 %0, %1, %2;" : "=r"(r) : "r"(addr), "r"(rank));
    return r;
}
__device__ __forceinline__ void st_async_v2(uint32_t addr, float a, float b, uint32_t bar) {
    asm volatile("st.async.weak.shared::cluster.mbarrier::complete_tx::bytes.v2.f32 [%0], {%1,%2}, [%3];"
                 ::"r"(addr), "f"(a), "f"(b), "r"(bar) : "memory");
}
__device__ __forceinline__ void st_async_v4(uint32_t addr, uint32_t a, uint32_t b, uint32_t c, uint32_t d, uint32_t bar) {
    asm volatile("st.async.weak.shared::cluster.mbarrier::complete_tx::bytes.v4.b32 [%0], {%1,%2,%3,%4}, [%5];"
                 ::"r"(addr), "r"(a), "r"(b), "r"(c), "r"(d), "r"(bar) : "memory");
}
__device__ __forceinline__ void progress_tick() {
    asm volatile("red.relaxed.gpu.global.inc.u32 [%0], %1;" ::"l"(&g_progress), "r"(kProgressTotal - 1) : "memory");
}
__device__ __forceinline__ int read_progress() {
    int v;
    asm volatile("ld.relaxed.gpu.global.u32 %0, [%1];" : "=r"(v) : "l"(&g_progress) : "memory");
    return v;
}
__device__ __forceinline__ float row_max(uint32_t addr) {
    const float4 a = lds128(addr), b = lds128(addr + 16);
    return fmaxf(fmaxf(fmaxf(a.x, a.y), fmaxf(a.z, a.w)), fmaxf(fmaxf(b.x, b.y), fmaxf(b.z, b.w)));
}
__device__ __forceinline__ float row_sum(uint32_t addr) {
    const float4 a = lds128(addr), b = lds128(addr + 16);
    return ((a.x + a.y) + (a.z + a.w)) + ((b.x + b.y) + (b.z + b.w));
}

__device__ __forceinline__ void issue_unit(uint32_t smem, int stage, int u, int group0,
                                           const CUtensorMap* kmap, const CUtensorMap* vmap) {
    const CUtensorMap* map = (u % (2 * G)) < G ? kmap : vmap;
    const int group = group0 + ((u / (2 * G)) * G + u % G) * kGroupsPerTile;
    const uint32_t bar = smem + kBarFull + 8 * kBoxes * stage;
    const uint32_t dst = smem + stage * kUnitBytes;
#pragma unroll
    for (int b = 0; b < kBoxes; ++b) {
        mbar_expect_tx(bar + 8 * b, kBoxBytes);
        tma_load_box(dst + b * kBoxBytes, map, group + b * kGroupsPerBox, bar + 8 * b);
    }
}

__global__ void __cluster_dims__(2, 1, 1) __launch_bounds__(kThreads, 1)
attn_kernel(const __nv_bfloat16* __restrict__ q, const __nv_bfloat16* __restrict__ k,
            const __nv_bfloat16* __restrict__ v, __nv_bfloat16* __restrict__ out,
            const __grid_constant__ CUtensorMap kmap, const __grid_constant__ CUtensorMap vmap) {
    extern __shared__ __align__(128) unsigned char smem_raw[];
    const uint32_t smem = ((uint32_t)__cvta_generic_to_shared(smem_raw) + 1023u) & ~1023u;
    const int warp = threadIdx.x >> 5;
    const int lane = threadIdx.x & 31;
    const int cta = blockIdx.x;
    const int head = cta >> 1;
    const uint32_t rank = cta & 1;
    const int group0 = cta * (kTiles * kGroupsPerTile);

    if (warp == 0 && elect_one()) prefetch_l2(k + (size_t)group0 * 8 * kD, kUnitBytes);
    if (warp == 2 && elect_one()) prefetch_l2(v + (size_t)group0 * 8 * kD, kD * 2);
    if (warp == 1 && elect_one()) {
#pragma unroll
        for (int b = 0; b < kBoxes; ++b) mbar_init(smem + kBarFull + 8 * b, 1);
        mbar_init_fence();
        issue_unit(smem, 0, 0, group0, &kmap, &vmap);
    }

    if (warp == kProducerWarp) {
        const bool leader = elect_one();
        int seen = 0;
        if (leader) {
            seen = read_progress();
            mbar_init(smem + kBarQ, 1);
            mbar_init_fence();
            mbar_expect_tx(smem + kBarQ, kRows * kD * 2);
#pragma unroll 4
            for (int r = 0; r < kRows; ++r)
                bulk_load(smem + kOffQ + r * kQStride, q + ((size_t)head * kRows + r) * kD, kD * 2, smem + kBarQ);
#pragma unroll 1
            for (int u = 1; u < kStages; ++u) {
#pragma unroll
                for (int b = 0; b < kBoxes; ++b) mbar_init(smem + kBarFull + 8 * (kBoxes * u + b), 1);
                mbar_init_fence();
                issue_unit(smem, u, u, group0, &kmap, &vmap);
            }
        }
        __syncwarp();
        cluster_sync_relaxed();
        if (leader) {
            int budget = kPollBudget;
            auto pace = [&](int need) {
                while (seen < need && budget > 0) {
                    const int now = read_progress();
                    seen = now < seen ? INT_MAX : now;
                    --budget;
                }
            };
            int stage = 0;
            uint32_t parity = 0;
#pragma unroll 1
            for (int u = kStages; u < kUnits - 1; ++u) {
                mbar_wait(smem + kBarEmpty + 8 * stage, parity);
                const int window = u <= kTaperStart
                    ? kWindow0 : kWindow0 - (kWindow0 - kWindow1) * (u - kTaperStart) / (kUnits - 1 - kTaperStart);
                pace(u * kCtas - window);
                issue_unit(smem, stage, u, group0, &kmap, &vmap);
                if (++stage == kStages) { stage = 0; parity ^= 1; }
            }
            mbar_wait(smem + kBarEmpty + 8 * kSlotLast, kParityLast ^ 1);
            mbar_wait(smem + kBarEmpty + 8 * (kSlotLast + 1), kParityLast ^ 1);
            mbar_wait_cluster(smem + kBarStat, 0);
#pragma unroll
            for (int b = 0; b < 2 * kBoxes; ++b) mbar_expect_tx(smem + kBarFull + 8 * (kBoxes * kSlotLast + b), kBoxBytes);
#pragma unroll
            for (int b = 0; b < kBoxes; ++b) {
                if (b % 2 == 0) pace((kUnits - 1) * kCtas - kWindow1 + (rank ? 0 : kLastRankDelay) + (b / 2) * kLastHalfDelay);
                tma_load_box_both(smem + (kSlotLast + rank) * kUnitBytes + b * kBoxBytes, &vmap,
                                  group0 + (kTiles - 1) * kGroupsPerTile + b * kGroupsPerBox,
                                  smem + kBarFull + 8 * (kBoxes * (kSlotLast + rank) + b));
            }
        }
        return;
    }

    if (warp == kMonitorWarp) {
        cluster_sync_relaxed();
        if (lane == 0) {
            int stage = 0;
            uint32_t parity = 0;
#pragma unroll 1
            for (int u = 0; u < kUnits - 1; ++u) {
#pragma unroll
                for (int b = 0; b < kBoxes; ++b) mbar_wait(smem + kBarFull + 8 * (kBoxes * stage + b), parity);
                progress_tick();
                mbar_arrive(smem + kBarEmpty + 8 * stage);
                if (++stage == kStages) { stage = 0; parity ^= 1; }
            }
        }
        return;
    }

    if (threadIdx.x == 3 * 32) {
        for (int s = 0; s < kStages; ++s) mbar_init(smem + kBarEmpty + 8 * s, kWarps + 1);
        mbar_init(smem + kBarStat, 1);
        mbar_init(smem + kBarPartial, 1 + kWarps / 2);
        mbar_init_fence();
        mbar_expect_tx(smem + kBarStat, kRows * 8 + kFragBytes);
        mbar_expect_tx(smem + kBarPartial, kRows * (kD / 2) * 4);
    }
    __syncwarp();
    cluster_sync_relaxed();

    const float c = 0.08838834764831845f * 1.4426950408889634f;
    const int g = lane >> 2;
    const int t4 = lane & 3;
    const int mi = lane >> 3;
    const int r8 = lane & 7;
    const uint32_t q_addr = smem + kOffQ + ((mi & 1) * 8 + r8) * kQStride + (mi >> 1) * 16;
    const uint32_t k_off = warp * 2 * kGroupBytes + r8 * 128 + ((mi ^ r8) << 4);
    const uint32_t k_bar = smem + kBarFull + 8 * (warp * 16 / kBoxKeys);
    const int vc = warp * 2 + (mi >> 1);
    const uint32_t v_off = (mi & 1) * kGroupBytes + (vc >> 3) * 1024 + r8 * 128 + (((vc & 7) ^ r8) << 4);
    const uint32_t stat_w = smem + kOffMax + (g * kWarps + warp) * 4;
    const uint32_t stat_r = smem + kOffMax + g * kWarps * 4;
    constexpr int kRow8 = 8 * kWarps * 4, kSum = kOffSum - kOffMax;
    const uint32_t p_w = smem + kOffP + threadIdx.x * 16;
    const uint32_t p_r = smem + kOffP + lane * 16;
    const uint32_t peer = map_to_cta(smem, rank ^ 1);
    uint64_t out_addr = __cvta_generic_to_global(out + ((size_t)head * kRows + g) * kD + rank * 64 + warp * 8 + t4 * 2);
    asm volatile("" : "+l"(out_addr));

    float m0 = -INFINITY, m1 = -INFINITY, l0 = 0.f, l1 = 0.f;
    float f0 = 0.f, f1 = 0.f, pf0 = 0.f, pf1 = 0.f;
    float o[2][2][4] = {};
    uint32_t pa[G - 1][8][4];

    mbar_wait(smem + kBarQ, 0);
    int stage = 0;
    uint32_t parity = 0;
#pragma unroll 1
    for (int st = 0; st < kSupers; ++st) {
        const bool last = st == kSupers - 1;

        uint32_t qa[8][4];
#pragma unroll
        for (int ks = 0; ks < 8; ++ks) ldsm_x4(qa[ks], q_addr + ks * 32);
        float s[G][2][4] = {};
#pragma unroll
        for (int i = 0; i < G; ++i) {
            mbar_wait(k_bar + 8 * kBoxes * stage, parity);
            const uint32_t base = smem + stage * kUnitBytes;
#pragma unroll
            for (int j = 0; j < 4; ++j) {
                uint32_t b[2][4];
#pragma unroll
                for (int n = 0; n < 2; ++n)
                    ldsm_x4(b[n], base + (k_off ^ ((j & 1) * 64)) + n * kGroupBytes + (j >> 1) * 1024);
#pragma unroll
                for (int n = 0; n < 2; ++n) mma_bf16(s[i][n], qa[2 * j], b[n][0], b[n][1]);
#pragma unroll
                for (int n = 0; n < 2; ++n) mma_bf16(s[i][n], qa[2 * j + 1], b[n][2], b[n][3]);
            }
            if (lane == 0) mbar_arrive(smem + kBarEmpty + 8 * stage);
            if (++stage == kStages) { stage = 0; parity ^= 1; }
        }

        float mx0 = m0, mx1 = m1;
#pragma unroll
        for (int i = 0; i < G; ++i)
#pragma unroll
            for (int n = 0; n < 2; ++n) {
                mx0 = fmaxf(mx0, fmaxf(s[i][n][0], s[i][n][1]));
                mx1 = fmaxf(mx1, fmaxf(s[i][n][2], s[i][n][3]));
            }
        mx0 = fmaxf(mx0, __shfl_xor_sync(0xffffffffu, mx0, 1));
        mx1 = fmaxf(mx1, __shfl_xor_sync(0xffffffffu, mx1, 1));
        mx0 = fmaxf(mx0, __shfl_xor_sync(0xffffffffu, mx0, 2));
        mx1 = fmaxf(mx1, __shfl_xor_sync(0xffffffffu, mx1, 2));
        if (t4 == 0) {
            sts32(stat_w, mx0);
            sts32(stat_w + kRow8, mx1);
        }
        compute_sync();
        const float mn0 = row_max(stat_r), mn1 = row_max(stat_r + kRow8);
        const float a0 = ex2((m0 - mn0) * c), a1 = ex2((m1 - mn1) * c);
        m0 = mn0;
        m1 = mn1;
        const float b0 = -mn0 * c, b1 = -mn1 * c;
        l0 *= a0;
        l1 *= a1;
#pragma unroll
        for (int i = 0; i < G; ++i) {
#pragma unroll
            for (int n = 0; n < 2; ++n) {
                s[i][n][0] = ex2(fmaf(s[i][n][0], c, b0));
                s[i][n][1] = ex2(fmaf(s[i][n][1], c, b0));
                s[i][n][2] = ex2(fmaf(s[i][n][2], c, b1));
                s[i][n][3] = ex2(fmaf(s[i][n][3], c, b1));
                l0 += s[i][n][0] + s[i][n][1];
                l1 += s[i][n][2] + s[i][n][3];
            }
            const uint32_t p0 = pack_bf16(s[i][0][0], s[i][0][1]), p1 = pack_bf16(s[i][0][2], s[i][0][3]);
            const uint32_t p2 = pack_bf16(s[i][1][0], s[i][1][1]), p3 = pack_bf16(s[i][1][2], s[i][1][3]);
            sts128(p_w + i * kFragBytes, p0, p1, p2, p3);
            if (i == G - 1 && last) st_async_v4(peer + kOffPeerP + threadIdx.x * 16, p0, p1, p2, p3, peer + kBarStat);
        }
        if (last) {
            l0 += __shfl_xor_sync(0xffffffffu, l0, 1);
            l1 += __shfl_xor_sync(0xffffffffu, l1, 1);
            l0 += __shfl_xor_sync(0xffffffffu, l0, 2);
            l1 += __shfl_xor_sync(0xffffffffu, l1, 2);
            if (t4 == 0) {
                sts32(stat_w + kSum, l0);
                sts32(stat_w + kSum + kRow8, l1);
            }
        }
#pragma unroll
        for (int h = 0; h < 2; ++h)
#pragma unroll
            for (int n = 0; n < 2; ++n) {
                o[h][n][0] *= a0; o[h][n][1] *= a0; o[h][n][2] *= a1; o[h][n][3] *= a1;
            }
        compute_sync();
        load_frags(pa[0], p_r);

        if (last) {
            l0 = row_sum(stat_r + kSum);
            l1 = row_sum(stat_r + kSum + kRow8);
            if (warp == 0 && t4 == 0) {
                st_async_v2(peer + kOffPeerStat + g * 8, m0, l0, peer + kBarStat);
                st_async_v2(peer + kOffPeerStat + g * 8 + 64, m1, l1, peer + kBarStat);
            }
            mbar_wait_cluster(smem + kBarStat, 0);
            const float2 x0 = lds64(smem + kOffPeerStat + g * 8), x1 = lds64(smem + kOffPeerStat + g * 8 + 64);
            const float mf0 = fmaxf(m0, x0.x), mf1 = fmaxf(m1, x1.x);
            const float e0 = ex2((m0 - mf0) * c), e1 = ex2((m1 - mf1) * c);
            const float pe0 = ex2((x0.x - mf0) * c), pe1 = ex2((x1.x - mf1) * c);
            const float r0 = 1.f / (l0 * e0 + x0.y * pe0), r1 = 1.f / (l1 * e1 + x1.y * pe1);
            f0 = e0 * r0;
            f1 = e1 * r1;
            pf0 = pe0 * r0;
            pf1 = pe1 * r1;
        }

        uint32_t vb[2][2][4];
        int prev_stage = stage;
        bool landed = false;
        auto pv_mma = [&](int y) {
#pragma unroll
            for (int h = 0; h < 2; ++h) {
                const uint32_t(&a)[4] = pa[(y / kBoxes) % (G - 1)][2 * (y % kBoxes) + h];
                mma_bf16(o[h][0], a, vb[y & 1][h][0], vb[y & 1][h][1]);
                mma_bf16(o[h][1], a, vb[y & 1][h][2], vb[y & 1][h][3]);
            }
        };
#pragma unroll
        for (int x = 0; x <= G * kBoxes; ++x) {
            const int bx = x % kBoxes;
            if (x == kBoxes) {
#pragma unroll
                for (int i = 1; i < G - 1; ++i) load_frags(pa[i], p_r + i * kFragBytes);
            }
            if (x == (G - 1) * kBoxes && last) {
                pv_mma(x - 1);
                break;
            }
            if (x < G * kBoxes) {
                if (!landed) mbar_wait(smem + kBarFull + 8 * (kBoxes * stage + bx), parity);
                __syncwarp();
                const uint32_t base = smem + stage * kUnitBytes + bx * kBoxBytes + v_off;
                if (bx == kBoxes - 1) {
                    prev_stage = stage;
                    if (++stage == kStages) { stage = 0; parity ^= 1; }
                }
                if (x + 1 < G * kBoxes) landed = mbar_test(smem + kBarFull + 8 * (kBoxes * stage + (bx + 1) % kBoxes), parity);
#pragma unroll
                for (int h = 0; h < 2; ++h) ldsm_x4_trans(vb[x & 1][h], base + h * 2 * kGroupBytes);
            }
            if (x > 0) {
                pv_mma(x - 1);
                if (bx == 0) {
                    if (lane == 0) mbar_arrive(smem + kBarEmpty + 8 * prev_stage);
                    constexpr int kOwn = (G - 1) * kFragBytes, kPeer = kOffPeerP - kOffP;
                    if (x == kBoxes) load_frags(pa[0], p_r + (last && !rank ? kPeer : kOwn));
                    if (x == 2 * kBoxes && last) load_frags(pa[1], p_r + (rank ? kPeer : kOwn));
                }
            }
        }
    }

    constexpr int kOffPartial = (kSlotLast + 2) * kUnitBytes, kHalf = kRows * (kD / 2) * 4;
    const bool mine = (warp >> 2) == rank;
#pragma unroll
    for (int n = 0; n < 2; ++n) {
        const uint32_t off = kOffPartial + ((2 * warp + n) & 7) * 512 + lane * 16;
        const uint32_t v0 = __float_as_uint((o[0][n][0] + o[1][n][0]) * f0), v1 = __float_as_uint((o[0][n][1] + o[1][n][1]) * f0);
        const uint32_t v2 = __float_as_uint((o[0][n][2] + o[1][n][2]) * f1), v3 = __float_as_uint((o[0][n][3] + o[1][n][3]) * f1);
        if (mine) sts128(smem + off, v0, v1, v2, v3);
        else st_async_v4(peer + off + kHalf, v0, v1, v2, v3, peer + kBarPartial);
    }
    __syncwarp();
    if (mine && lane == 0) mbar_arrive(smem + kBarPartial);

    const uint32_t w_addr = smem + mi * kGroupBytes + rank * 1024 + r8 * 128 + ((warp ^ r8) << 4);
    const uint32_t part = smem + kOffPartial + threadIdx.x * 16;
    const float ga0 = rank ? f0 : pf0, ga1 = rank ? f1 : pf1, gb0 = rank ? pf0 : f0, gb1 = rank ? pf1 : f1;
    float acc[2][2][4] = {};
    uint32_t wb[2][4] = {};
    bool landed = false, early = false;
    float4 x0, x1;
    auto slot_of = [](int x) { return kSlotLast + 1 - x / kBoxes; };
    auto bar_of = [&](int x) { return smem + kBarFull + 8 * (kBoxes * slot_of(x) + x % kBoxes); };
    auto last_mma = [&](int y) {
        mma_bf16(acc[y / kBoxes][0], pa[y / kBoxes][2 * (y % kBoxes)], wb[y & 1][0], wb[y & 1][1]);
        mma_bf16(acc[y / kBoxes][1], pa[y / kBoxes][2 * (y % kBoxes) + 1], wb[y & 1][2], wb[y & 1][3]);
    };
#pragma unroll
    for (int x = 0; x <= 2 * kBoxes; ++x) {
        const bool final_box = x == 2 * kBoxes - 1;
        if (final_box) {
            last_mma(x - 1);
            early = mbar_test_cluster(smem + kBarPartial, 0);
            if (early) {
                x0 = lds128(part);
                x1 = lds128(part + kHalf);
            }
        }
        if (x < 2 * kBoxes) {
            if (!landed) mbar_wait(bar_of(x), kParityLast);
            __syncwarp();
            if (!final_box) landed = mbar_test(bar_of(x + 1), kParityLast);
            ldsm_x4_trans(wb[x & 1], w_addr + slot_of(x) * kUnitBytes + (x % kBoxes) * kBoxBytes);
        }
        if (x > 0 && !final_box) last_mma(x - 1);
    }
    if (!early) {
        mbar_wait_cluster(smem + kBarPartial, 0);
        x0 = lds128(part);
        x1 = lds128(part + kHalf);
    }
    const float r0 = fmaf(acc[1][0][0] + acc[1][1][0], gb0, fmaf(acc[0][0][0] + acc[0][1][0], ga0, x0.x + x1.x));
    const float r1 = fmaf(acc[1][0][1] + acc[1][1][1], gb0, fmaf(acc[0][0][1] + acc[0][1][1], ga0, x0.y + x1.y));
    const float r2 = fmaf(acc[1][0][2] + acc[1][1][2], gb1, fmaf(acc[0][0][2] + acc[0][1][2], ga1, x0.z + x1.z));
    const float r3 = fmaf(acc[1][0][3] + acc[1][1][3], gb1, fmaf(acc[0][0][3] + acc[0][1][3], ga1, x0.w + x1.w));
    stg32(out_addr, pack_bf16(r0, r1));
    stg32(out_addr + 8 * kD * 2, pack_bf16(r2, r3));
}

typedef CUresult (*EncodeTiledFn)(CUtensorMap*, CUtensorMapDataType, cuuint32_t, void*, const cuuint64_t*,
                                  const cuuint64_t*, const cuuint32_t*, const cuuint32_t*, CUtensorMapInterleave,
                                  CUtensorMapSwizzle, CUtensorMapL2promotion, CUtensorMapFloatOOBfill);

inline CUtensorMap make_map(const void* ptr) {
    static EncodeTiledFn encode = nullptr;
    if (!encode) {
        cudaDriverEntryPointQueryResult status;
        cudaGetDriverEntryPoint("cuTensorMapEncodeTiled", (void**)&encode, cudaEnableDefault, &status);
    }
    CUtensorMap map;
    const cuuint64_t dims[4] = {64, 8, 2, (cuuint64_t)kHeads * kSk / 8};
    const cuuint64_t strides[3] = {kD * 2, 128, kGroupBytes};
    const cuuint32_t box[4] = {64, 8, 2, kGroupsPerBox};
    const cuuint32_t elem_strides[4] = {1, 1, 1, 1};
    encode(&map, CU_TENSOR_MAP_DATA_TYPE_BFLOAT16, 4, const_cast<void*>(ptr), dims, strides, box, elem_strides,
           CU_TENSOR_MAP_INTERLEAVE_NONE, CU_TENSOR_MAP_SWIZZLE_128B, CU_TENSOR_MAP_L2_PROMOTION_NONE,
           CU_TENSOR_MAP_FLOAT_OOB_FILL_NONE);
    return map;
}

}

extern "C" void kernel_launch(void* const* d_in, const int* in_sizes, int n_in, void* d_out, int out_size) {
    (void)in_sizes; (void)n_in; (void)out_size;
    cudaFuncSetAttribute(gqa::attn_kernel, cudaFuncAttributeMaxDynamicSharedMemorySize, gqa::kSmemBytes);
    gqa::attn_kernel<<<gqa::kCtas, gqa::kThreads, gqa::kSmemBytes>>>(
        (const __nv_bfloat16*)d_in[0], (const __nv_bfloat16*)d_in[1], (const __nv_bfloat16*)d_in[2],
        (__nv_bfloat16*)d_out, gqa::make_map(d_in[1]), gqa::make_map(d_in[2]));
}
```
